```python
import torch

def _softmax(x, axis=-1):
    return torch.softmax(x, dim=axis)

def _gelu(x):
    return torch.nn.functional.gelu(x, approximate='tanh')

def _silu(x):
    return torch.nn.functional.silu(x)

def _sigmoid(x):
    return torch.sigmoid(x)

def _layernorm(x, axis=-1, eps=1e-05):
    m = x.mean(dim=axis, keepdim=True)
    v = x.var(dim=axis, keepdim=True, unbiased=False)
    return (x - m) / torch.sqrt(v + eps)

def _scatter_add(tgt, idx, src, axis=0):
    return tgt.clone().index_add_(axis, idx, src)

def _segment_sum(src, seg, n):
    out = torch.zeros((n,) + src.shape[1:], dtype=src.dtype)
    return out.index_add_(0, seg, src)

def _pad(x, pw):
    flat = tuple((v for pair in reversed(pw) for v in pair))
    return torch.nn.functional.pad(x, flat)
kernel_name = 'adaLN_cond__gqa_block_cached__geglu_ffn__decode'

def setup_inputs():

    _w = lambda a: (lambda t: t.to(torch.bfloat16) if t.is_floating_point() else t)(torch.as_tensor(a))

    def _A_setup():
        B, Sq, D = (4, 1, 576)
        Hq, Hkv, Sk, Dh = (32, 16, 4096, 128)
        assert Hq % Hkv == 0, (Hq, Hkv)
        return {'x': _w((lambda *s: torch.randn(*s, dtype=torch.bfloat16) * 0.1)(B, Sq, D)), 'k_cache': _w((lambda *s: torch.randn(*s, dtype=torch.bfloat16) * 0.8)(B, Hkv, Sk, Dh)), 'v_cache': _w((lambda *s: torch.randn(*s, dtype=torch.bfloat16) * 1.6)(B, Hkv, Sk, Dh)), 'wq': _w((lambda *s: torch.randn(*s, dtype=torch.bfloat16) * 0.8)(D, Hq * Dh) * D ** (-0.5)), 'wo': _w((lambda *s: torch.randn(*s, dtype=torch.bfloat16) * 1.6)(Hq * Dh, D) * (Hq * Dh) ** (-0.5))}
    _A_in = _A_setup()

    def _B_setup():
        B, S, D, F = (4, 1, 576, 4608)
        return {'x': _w((lambda *s: torch.randn(*s, dtype=torch.bfloat16) * 0.1)(B, S, D)), 'w_gate': _w((lambda *s: torch.randn(*s, dtype=torch.bfloat16) * 0.1)(D, F)), 'w_up': _w((lambda *s: torch.randn(*s, dtype=torch.bfloat16) * 0.1)(D, F)), 'w_down': _w((lambda *s: torch.randn(*s, dtype=torch.bfloat16) * 0.1)(F, D))}
    _B_in = _B_setup()
    return {'A_x': _A_in['x'], 'A_k_cache': _A_in['k_cache'], 'A_v_cache': _A_in['v_cache'], 'A_wq': _A_in['wq'], 'A_wo': _A_in['wo'], 'B_x': _B_in['x'], 'B_w_gate': _B_in['w_gate'], 'B_w_up': _B_in['w_up'], 'B_w_down': _B_in['w_down'], 'c': _w((lambda *s: torch.randn(*s, dtype=torch.bfloat16) * 0.8)(4, 576) * 8.0), 'w_mod': _w((lambda *s: torch.randn(*s, dtype=torch.bfloat16) * 0.8)(576, 6 * 576) * 576 ** (-0.5) * 8.0)}

def reference(A_x, A_k_cache, A_v_cache, A_wq, A_wo, B_x, B_w_gate, B_w_up, B_w_down, c, w_mod):

    def _A_ref(x, k_cache, v_cache, wq, wo):
        B, Sq, D = x.shape
        Hq, Dh = (32, 128)
        Hkv = k_cache.shape[1]
        rep = Hq // Hkv
        q = (lambda x, *d: x.permute(*d))((x @ wq).reshape(B, Sq, Hq, Dh), 0, 2, 1, 3)
        k = (lambda x, n, axis: torch.repeat_interleave(x, n, dim=axis))(k_cache, rep, axis=1)
        v = (lambda x, n, axis: torch.repeat_interleave(x, n, dim=axis))(v_cache, rep, axis=1)
        scores = torch.einsum('bhqd,bhkd->bhqk', q, k) * Dh ** (-0.5)
        p = _softmax(scores, axis=-1)
        o = torch.einsum('bhqk,bhkd->bhqd', p, v)
        return (lambda x, *d: x.permute(*d))(o, 0, 2, 1, 3).reshape(B, Sq, Hq * Dh) @ wo

    def _B_ref(x, w_gate, w_up, w_down):
        return _gelu(x @ w_gate) * (x @ w_up) @ w_down
    x = A_x
    mod = (_silu(c) @ w_mod).reshape(c.shape[0], 6, 1, -1)
    sa, ca, ga, sb, cb, gb = (mod[:, 0].clone(), mod[:, 1].clone(), mod[:, 2].clone(), mod[:, 3].clone(), mod[:, 4].clone(), mod[:, 5].clone())
    h = _layernorm(x, axis=-1) * (1 + ca) + sa
    x = x + ga * _A_ref(h, A_k_cache, A_v_cache, A_wq, A_wo)
    h = _layernorm(x, axis=-1) * (1 + cb) + sb
    x = x + gb * _B_ref(h, B_w_gate, B_w_up, B_w_down)
    return x
```

```cpp
#include <cuda_runtime.h>
#include <cuda_bf16.h>
#include <cuda.h>
#include <stdint.h>

namespace {

constexpr int D_MODEL = 576;
constexpr int NB = 4;
constexpr int SK = 4096;
constexpr int FF = 4608;
constexpr int NCTA = 128;
constexpr int NTHREADS = 288;
constexpr int NSLOT = 12;
constexpr int TILE_BYTES = 16384;
constexpr int TILES = 32;
constexpr int AV_PITCH = 1168;

constexpr int SM_WMOD = 7 * TILE_BYTES;
constexpr int SM_WQ = SM_WMOD + 36864;
constexpr int SM_WO = 4 * TILE_BYTES;
constexpr int SM_WG = SM_WO + 36864;
constexpr int SM_WU = SM_WG + 46080;
constexpr int SM_WD = 0;
constexpr int SM_SC = NSLOT * TILE_BYTES;
constexpr int SM_RED = SM_SC + 8192;
constexpr int SM_AVA = SM_RED + 8192;
constexpr int SM_AVB = SM_AVA + 4 * AV_PITCH;
constexpr int SM_CB1 = SM_AVB + 4 * AV_PITCH;
constexpr int SM_SB = SM_CB1 + 4608;
constexpr int SM_QS = SM_SB + 4608;
constexpr int SM_BAR = SM_QS + 512;
constexpr int SM_TOTAL = SM_BAR + 256;
static_assert(SM_TOTAL <= 232448, "smem");
constexpr int BAR_FULL = 0, BAR_EMPTY = 12, BAR_WMOD = 24, BAR_WQ = 25, BAR_WO = 26, BAR_WGU = 27, BAR_WD = 28;

constexpr unsigned SPIN_LIMIT = 1u << 22;

struct Maps {
    CUtensorMap k, v, wmod16, wmod32, wq, wo, wg, wu;
};

__device__ uint4 g_h[288];
__device__ uint4 g_mod[1152];
__device__ uint4 g_q[2048];
__device__ uint4 g_stat[NCTA * 2];
__device__ uint4 g_opart[NCTA * 64];
__device__ uint4 g_wpart[72 * 16 * 8];
__device__ uint4 g_x1[288];
__device__ uint4 g_fpart[72 * NCTA * 8];
#define STAMP(i)
#define STAMP0(i)

__device__ __forceinline__ uint32_t enc(uint32_t w) { return ~(w == 0xFFFFFFFFu ? 0x7FFF7FFFu : w); }
__device__ __forceinline__ uint32_t encf(float f) { return enc(__float_as_uint(f)); }
__device__ __forceinline__ float decf(uint32_t w) { return __uint_as_float(~w); }
__device__ __forceinline__ float bfr(float x) { return __bfloat162float(__float2bfloat16_rn(x)); }
__device__ __forceinline__ float bf_lo(uint32_t w) { return __uint_as_float(w << 16); }
__device__ __forceinline__ float bf_hi(uint32_t w) { return __uint_as_float(w & 0xFFFF0000u); }
__device__ __forceinline__ uint32_t pack_bf(float lo, float hi) {
    uint32_t r;
    asm("cvt.rn.bf16x2.f32 %0, %1, %2;" : "=r"(r) : "f"(hi), "f"(lo));
    return r;
}
__device__ __forceinline__ void mbar_init(uint32_t bar, uint32_t cnt) {
    asm volatile("mbarrier.init.shared::cta.b64 [%0], %1;" ::"r"(bar), "r"(cnt) : "memory");
}
__device__ __forceinline__ void mbar_expect(uint32_t bar, uint32_t bytes) {
    asm volatile("mbarrier.arrive.expect_tx.shared::cta.b64 _, [%0], %1;" ::"r"(bar), "r"(bytes) : "memory");
}
__device__ __forceinline__ void mbar_arrive(uint32_t bar) {
    asm volatile("mbarrier.arrive.shared::cta.b64 _, [%0];" ::"r"(bar) : "memory");
}
__device__ __forceinline__ void mbar_arrive_n(uint32_t bar, uint32_t n) {
    asm volatile("mbarrier.arrive.shared::cta.b64 _, [%0], %1;" ::"r"(bar), "r"(n) : "memory");
}
__device__ __forceinline__ void mbar_wait(uint32_t bar, uint32_t parity) {
    for (unsigned it = 0;; it++) {
        uint32_t ok;
        asm volatile("{\n.reg .pred p;\nmbarrier.try_wait.parity.shared::cta.b64 p, [%1], %2;\nselp.u32 %0, 1, 0, p;\n}"
                     : "=r"(ok) : "r"(bar), "r"(parity) : "memory");
        if (ok) break;
        if (it > SPIN_LIMIT) __trap();
    }
}
__device__ __forceinline__ void tma2(uint32_t dst, const CUtensorMap* m, int c0, int c1, uint32_t bar) {
    asm volatile("cp.async.bulk.tensor.2d.shared::cluster.global.mbarrier::complete_tx::bytes [%0], [%1, {%3, %4}], [%2];"
                 ::"r"(dst), "l"(m), "r"(bar), "r"(c0), "r"(c1) : "memory");
}
__device__ __forceinline__ void tma3(uint32_t dst, const CUtensorMap* m, int c0, int c1, int c2, uint32_t bar) {
    asm volatile("cp.async.bulk.tensor.3d.shared::cluster.global.mbarrier::complete_tx::bytes [%0], [%1, {%3, %4, %5}], [%2];"
                 ::"r"(dst), "l"(m), "r"(bar), "r"(c0), "r"(c1), "r"(c2) : "memory");
}
__device__ __forceinline__ void bulk1(uint32_t dst, const void* src, uint32_t bytes, uint32_t bar) {
    asm volatile("cp.async.bulk.shared::cluster.global.mbarrier::complete_tx::bytes [%0], [%1], %2, [%3];"
                 ::"r"(dst), "l"(src), "r"(bytes), "r"(bar) : "memory");
}
__device__ __forceinline__ void cbar() { asm volatile("bar.sync 1, 256;" ::: "memory"); }
__device__ __forceinline__ void ldsm4(uint32_t (&r)[4], uint32_t a) {
    asm volatile("ldmatrix.sync.aligned.m8n8.x4.shared.b16 {%0,%1,%2,%3}, [%4];"
                 : "=r"(r[0]), "=r"(r[1]), "=r"(r[2]), "=r"(r[3]) : "r"(a) : "memory");
}
__device__ __forceinline__ void ldsm4t(uint32_t (&r)[4], uint32_t a) {
    asm volatile("ldmatrix.sync.aligned.m8n8.x4.trans.shared.b16 {%0,%1,%2,%3}, [%4];"
                 : "=r"(r[0]), "=r"(r[1]), "=r"(r[2]), "=r"(r[3]) : "r"(a) : "memory");
}
__device__ __forceinline__ void ldsm2t(uint32_t (&r)[2], uint32_t a) {
    asm volatile("ldmatrix.sync.aligned.m8n8.x2.trans.shared.b16 {%0,%1}, [%2];"
                 : "=r"(r[0]), "=r"(r[1]) : "r"(a) : "memory");
}
__device__ __forceinline__ void mma16816(float (&c)[4], const uint32_t (&a)[4], uint32_t b0, uint32_t b1) {
    asm volatile("mma.sync.aligned.m16n8k16.row.col.f32.bf16.bf16.f32 {%0,%1,%2,%3}, {%4,%5,%6,%7}, {%8,%9}, {%0,%1,%2,%3};"
                 : "+f"(c[0]), "+f"(c[1]), "+f"(c[2]), "+f"(c[3])
                 : "r"(a[0]), "r"(a[1]), "r"(a[2]), "r"(a[3]), "r"(b0), "r"(b1));
}
__device__ __forceinline__ void mma1688(float (&c)[4], const uint32_t (&a)[2], uint32_t b0) {
    asm volatile("mma.sync.aligned.m16n8k8.row.col.f32.bf16.bf16.f32 {%0,%1,%2,%3}, {%4,%5}, {%6}, {%0,%1,%2,%3};"
                 : "+f"(c[0]), "+f"(c[1]), "+f"(c[2]), "+f"(c[3]) : "r"(a[0]), "r"(a[1]), "r"(b0));
}
__device__ __forceinline__ uint32_t lds32(uint32_t a) {
    uint32_t r; asm volatile("ld.shared.b32 %0, [%1];" : "=r"(r) : "r"(a) : "memory"); return r;
}
__device__ __forceinline__ float ldsf(uint32_t a) { return __uint_as_float(lds32(a)); }
__device__ __forceinline__ uint4 lds128(uint32_t a) {
    uint4 r; asm volatile("ld.shared.v4.b32 {%0,%1,%2,%3}, [%4];" : "=r"(r.x), "=r"(r.y), "=r"(r.z), "=r"(r.w) : "r"(a) : "memory"); return r;
}
__device__ __forceinline__ float4 lds128f(uint32_t a) {
    float4 r; asm volatile("ld.shared.v4.f32 {%0,%1,%2,%3}, [%4];" : "=f"(r.x), "=f"(r.y), "=f"(r.z), "=f"(r.w) : "r"(a) : "memory"); return r;
}
__device__ __forceinline__ void sts16(uint32_t a, uint32_t v) { asm volatile("st.shared.b16 [%0], %1;" ::"r"(a), "h"((unsigned short)v) : "memory"); }
__device__ __forceinline__ void sts32(uint32_t a, uint32_t v) { asm volatile("st.shared.b32 [%0], %1;" ::"r"(a), "r"(v) : "memory"); }
__device__ __forceinline__ void stsf(uint32_t a, float v) { sts32(a, __float_as_uint(v)); }
__device__ __forceinline__ void sts128(uint32_t a, uint4 v) {
    asm volatile("st.shared.v4.b32 [%0], {%1,%2,%3,%4};" ::"r"(a), "r"(v.x), "r"(v.y), "r"(v.z), "r"(v.w) : "memory");
}
__device__ __forceinline__ void sts128f(uint32_t a, float x, float y, float z, float w) {
    asm volatile("st.shared.v4.f32 [%0], {%1,%2,%3,%4};" ::"r"(a), "f"(x), "f"(y), "f"(z), "f"(w) : "memory");
}
__device__ __forceinline__ void pub32(void* p, uint32_t v) { asm volatile("st.relaxed.gpu.global.b32 [%0], %1;" ::"l"(p), "r"(v) : "memory"); }
__device__ __forceinline__ void pub64(void* p, uint32_t a, uint32_t b) { asm volatile("st.relaxed.gpu.global.v2.b32 [%0], {%1,%2};" ::"l"(p), "r"(a), "r"(b) : "memory"); }
__device__ __forceinline__ void pub128(void* p, uint4 v) {
    asm volatile("st.relaxed.gpu.global.v4.b32 [%0], {%1,%2,%3,%4};" ::"l"(p), "r"(v.x), "r"(v.y), "r"(v.z), "r"(v.w) : "memory");
}
__device__ __forceinline__ uint4 ldg_rlx(const uint4* p) {
    uint4 r; asm volatile("ld.relaxed.gpu.global.v4.b32 {%0,%1,%2,%3}, [%4];" : "=r"(r.x), "=r"(r.y), "=r"(r.z), "=r"(r.w) : "l"(p) : "memory"); return r;
}
__device__ __forceinline__ bool ready(const uint4& v) { return v.x != 0 && v.y != 0 && v.z != 0 && v.w != 0; }
template <int N, int SLEEP>
__device__ __forceinline__ void poll(uint4 (&v)[N], const uint4* p, int stride) {
#pragma unroll
    for (int i = 0; i < N; i++) v[i] = ldg_rlx(p + i * stride);
    for (unsigned it = 0;; it++) {
        bool ok = true;
#pragma unroll
        for (int i = 0; i < N; i++) ok = ok && ready(v[i]);
        if (ok) break;
        if (it > SPIN_LIMIT) __trap();
        if (SLEEP) __nanosleep(SLEEP);
#pragma unroll
        for (int i = 0; i < N; i++) if (!ready(v[i])) v[i] = ldg_rlx(p + i * stride);
    }
}
__device__ __forceinline__ uint4 unzip(const uint4& e) {
    uint4 r;
    r.x = __byte_perm(~e.x, ~e.z, 0x5410);
    r.y = __byte_perm(~e.x, ~e.z, 0x7632);
    r.z = __byte_perm(~e.y, ~e.w, 0x5410);
    r.w = __byte_perm(~e.y, ~e.w, 0x7632);
    return r;
}
template <int SLEEP>
__device__ __forceinline__ void gather576(const uint4* src, uint32_t dst, int pitch, int tid) {
    if (tid < 144) {
        uint4 v[2];
        poll<2, SLEEP>(v, src + tid, 144);
#pragma unroll
        for (int i = 0; i < 2; i++) {
            uint4 u = unzip(v[i]);
            uint32_t a = dst + (tid + 144 * i) * 4;
            sts32(a, u.x); sts32(a + pitch, u.y); sts32(a + 2 * pitch, u.z); sts32(a + 3 * pitch, u.w);
        }
    }
}
__device__ __forceinline__ float warp_sum(float v) {
#pragma unroll
    for (int o = 16; o; o >>= 1) v += __shfl_xor_sync(0xffffffffu, v, o);
    return v;
}
__device__ __forceinline__ float warp_max(float v) {
#pragma unroll
    for (int o = 16; o; o >>= 1) v = fmaxf(v, __shfl_xor_sync(0xffffffffu, v, o));
    return v;
}
__device__ __forceinline__ void ln_stats(const uint32_t (&w)[9], float& mean_b, float& den_b) {
    float s = 0.f;
#pragma unroll
    for (int i = 0; i < 9; i++) s += bf_lo(w[i]) + bf_hi(w[i]);
    const float mean = warp_sum(s) * (1.0f / D_MODEL);
    float q = 0.f;
#pragma unroll
    for (int i = 0; i < 9; i++) {
        float a = bf_lo(w[i]) - mean, b = bf_hi(w[i]) - mean;
        q += a * a + b * b;
    }
    const float var = warp_sum(q) * (1.0f / D_MODEL);
    mean_b = bfr(mean);
    den_b = bfr(sqrtf(bfr(bfr(var) + 1e-5f)));
}
__device__ __forceinline__ float ln_apply(float x, float mean_b, float den_b) { return bfr(__fdiv_rn(bfr(x - mean_b), den_b)); }

__device__ __forceinline__ float4 gemv576x32(uint32_t a0, uint32_t a1, uint32_t kstep_bytes, uint32_t av, uint32_t red, int warp, int lane) {
    float c0[4] = {0.f, 0.f, 0.f, 0.f}, c1[4] = {0.f, 0.f, 0.f, 0.f};
    const uint32_t bb = av + ((lane >> 2) & 3) * AV_PITCH + (lane & 3) * 4;
#pragma unroll
    for (int i = 0; i < 5; i++) {
        const int ks = warp + 8 * i;
        if (ks < 36) {
            uint32_t x[4], y[4];
            ldsm4t(x, a0 + ks * kstep_bytes);
            ldsm4t(y, a1 + ks * kstep_bytes);
            const uint32_t b0 = lds32(bb + ks * 32), b1 = lds32(bb + ks * 32 + 16);
            mma16816(c0, x, b0, b1);
            mma16816(c1, y, b0, b1);
        }
    }
    const bool t1 = (lane & 2) != 0;
    sts128f(red + warp * 512 + (t1 ? 256 : 0) + ((lane >> 2) * 2 + (lane & 1)) * 16,
            t1 ? c1[0] : c0[0], t1 ? c1[1] : c0[1], t1 ? c1[2] : c0[2], t1 ? c1[3] : c0[3]);
    cbar();
    float4 r = make_float4(0.f, 0.f, 0.f, 0.f);
    if (warp == 0) {
#pragma unroll
        for (int w = 0; w < 8; w++) {
            float4 v = lds128f(red + w * 512 + lane * 16);
            r.x += v.x; r.y += v.y; r.z += v.z; r.w += v.w;
        }
    }
    return r;
}

__global__ void __launch_bounds__(NTHREADS, 1)
fused_block_kernel(const __grid_constant__ Maps maps, const __nv_bfloat16* __restrict__ x, const __nv_bfloat16* __restrict__ cvec,
                   const __nv_bfloat16* __restrict__ w_down, __nv_bfloat16* __restrict__ out) {
    extern __shared__ __align__(1024) unsigned char smem_raw[];
    const uint32_t sm = (uint32_t)__cvta_generic_to_shared(smem_raw);
    const uint32_t bars = sm + SM_BAR;
    const int tid = threadIdx.x, warp = tid >> 5, lane = tid & 31;
    const int cta = blockIdx.x;
    const int g = cta >> 3, j = cta & 7, b = j >> 1, s = j & 1;
    const int nblk = (cta & 1) ? 4 : 5;
    const int f0 = (cta >> 1) * 72 + (cta & 1) * 40;

    if (tid == 256) {
        if (sm & 1023) __trap();
        for (int i = 0; i < NSLOT; i++) { mbar_init(bars + (BAR_FULL + i) * 8, 1); mbar_init(bars + (BAR_EMPTY + i) * 8, 2); }
        for (int i = BAR_WMOD; i <= BAR_WD; i++) mbar_init(bars + i * 8, 1);
        asm volatile("fence.mbarrier_init.release.cluster;" ::: "memory");
        if (cta < 36) {
            mbar_expect(bars + BAR_WMOD * 8, 36864);
            for (int i = 0; i < 3; i++) {
                tma2(sm + SM_WMOD + i * 6144, &maps.wmod16, cta * 16, i * 192, bars + BAR_WMOD * 8);
                tma2(sm + SM_WMOD + 18432 + i * 6144, &maps.wmod16, D_MODEL + cta * 16, i * 192, bars + BAR_WMOD * 8);
            }
        } else if (cta < 108) {
            mbar_expect(bars + BAR_WMOD * 8, 36864);
            for (int i = 0; i < 3; i++)
                tma2(sm + SM_WMOD + i * 12288, &maps.wmod32, 2 * D_MODEL + (cta - 36) * 32, i * 192, bars + BAR_WMOD * 8);
        }
        mbar_expect(bars + BAR_WQ * 8, 36864);
        for (int i = 0; i < 3; i++) tma2(sm + SM_WQ + i * 12288, &maps.wq, cta * 32, i * 192, bars + BAR_WQ * 8);
    }
    STAMP0(0);
    __syncthreads();

    if (warp == 8) {
        const int row0 = (b * 16 + g) * SK + s * 64;
        if (lane == 0) {
            for (int i = 0; i < 2 * TILES; i++) {
                const int slot = i % NSLOT, n = i / NSLOT;
                if (slot >= 7) mbar_wait(bars + (BAR_EMPTY + slot) * 8, n & 1);
                else if (n >= 1) mbar_wait(bars + (BAR_EMPTY + slot) * 8, (n - 1) & 1);
                mbar_expect(bars + (BAR_FULL + slot) * 8, TILE_BYTES);
                tma3(sm + slot * TILE_BYTES, i < TILES ? &maps.k : &maps.v, 0, row0 + (i & (TILES - 1)) * 128, 0, bars + (BAR_FULL + slot) * 8);
            }
            STAMP(16);
            const uint32_t e = bars + BAR_EMPTY * 8;
            mbar_expect(bars + BAR_WO * 8, 36864);
            mbar_expect(bars + BAR_WGU * 8, 92160);
            mbar_expect(bars + BAR_WD * 8, nblk * 8 * 1152);
            mbar_wait(e + 4 * 8, 0); mbar_wait(e + 5 * 8, 0);
            tma2(sm + SM_WO, &maps.wo, j * 72, g * 256, bars + BAR_WO * 8);
            mbar_wait(e + 6 * 8, 0);
            tma2(sm + SM_WO + 18432, &maps.wo, j * 72, g * 256 + 128, bars + BAR_WO * 8);
            mbar_wait(e + 7 * 8, 1);
            tma2(sm + SM_WG, &maps.wg, f0, 0, bars + BAR_WGU * 8);
            mbar_wait(e + 8 * 8, 1);
            tma2(sm + SM_WG + 15360, &maps.wg, f0, 192, bars + BAR_WGU * 8);
            mbar_wait(e + 9 * 8, 1);
            tma2(sm + SM_WG + 30720, &maps.wg, f0, 384, bars + BAR_WGU * 8);
            tma2(sm + SM_WU, &maps.wu, f0, 0, bars + BAR_WGU * 8);
            mbar_wait(e + 10 * 8, 1);
            tma2(sm + SM_WU + 15360, &maps.wu, f0, 192, bars + BAR_WGU * 8);
            mbar_wait(e + 11 * 8, 1);
            tma2(sm + SM_WU + 30720, &maps.wu, f0, 384, bars + BAR_WGU * 8);
            for (int sl = 0; sl < 3; sl++) {
                mbar_wait(e + sl * 8, 1);
                const int r1 = min(nblk * 8, (sl + 1) * 14);
                for (int r = sl * 14; r < r1; r++)
                    bulk1(sm + SM_WD + r * AV_PITCH, w_down + (size_t)(f0 + r) * D_MODEL, 1152, bars + BAR_WD * 8);
            }
            STAMP(17);
        }
        return;
    }

    const int mi = lane >> 3, r8 = lane & 7;
    if (cta < 108) {
        const uint32_t* c32 = reinterpret_cast<const uint32_t*>(cvec);
        for (int i = tid; i < NB * 288; i += 256) {
            const uint32_t w = __ldg(c32 + i);
            const float a = bf_lo(w), c = bf_hi(w);
            sts32(sm + SM_AVA + (i / 288) * AV_PITCH + (i % 288) * 4,
                  pack_bf(__fdiv_rn(a, 1.0f + __expf(-a)), __fdiv_rn(c, 1.0f + __expf(-c))));
        }
        if (cta < 36 && warp < 4) {
            const uint32_t* x32 = reinterpret_cast<const uint32_t*>(x) + warp * 288;
            uint32_t w[9];
#pragma unroll
            for (int i = 0; i < 9; i++) w[i] = __ldg(x32 + lane + 32 * i);
            float mean_b, den_b;
            ln_stats(w, mean_b, den_b);
#pragma unroll
            for (int i = 0; i < 9; i++)
                sts32(sm + SM_CB1 + warp * 1152 + (lane + 32 * i) * 4,
                      pack_bf(ln_apply(bf_lo(w[i]), mean_b, den_b), ln_apply(bf_hi(w[i]), mean_b, den_b)));
        }
        cbar();
        mbar_wait(bars + BAR_WMOD * 8, 0);
        STAMP0(1);
        uint32_t a0, a1, kb;
        const int k = (mi >> 1) * 8 + r8;
        if (cta < 36) {
            const uint32_t base = sm + SM_WMOD + (mi & 1) * 18432 + k * 32;
            a0 = base + ((0 ^ (r8 >> 2)) << 4); a1 = base + ((1 ^ (r8 >> 2)) << 4); kb = 512;
        } else {
            const uint32_t base = sm + SM_WMOD + k * 64;
            a0 = base + ((((mi & 1) * 2) ^ (r8 >> 1)) << 4); a1 = base + ((((mi & 1) * 2 + 1) ^ (r8 >> 1)) << 4); kb = 1024;
        }
        const float4 r = gemv576x32(a0, a1, kb, sm + SM_AVA, sm + SM_RED, warp, lane);
        if (warp == 0) {
            const int col = lane >> 1, bp = lane & 1;
            if (cta < 36) {
                const int d = cta * 16 + col;
                const unsigned char* xn = smem_raw + SM_CB1 + d * 2;
                const float n0 = __bfloat162float(*reinterpret_cast<const __nv_bfloat16*>(xn + (2 * bp) * 1152));
                const float n1 = __bfloat162float(*reinterpret_cast<const __nv_bfloat16*>(xn + (2 * bp + 1) * 1152));
                const float h0 = bfr(n0 * bfr(1.0f + bfr(r.z))) + bfr(r.x);
                const float h1 = bfr(n1 * bfr(1.0f + bfr(r.w))) + bfr(r.y);
                pub32(reinterpret_cast<uint32_t*>(g_h) + cta * 32 + lane, enc(pack_bf(h0, h1)));
            } else {
                uint32_t* dst = reinterpret_cast<uint32_t*>(g_mod) + (cta - 36) * 64 + lane;
                pub32(dst, enc(pack_bf(r.x, r.y)));
                pub32(dst + 32, enc(pack_bf(r.z, r.w)));
            }
        }
    }
    if (tid == 0) { mbar_arrive_n(bars + (BAR_EMPTY + 7) * 8, 2); mbar_arrive_n(bars + (BAR_EMPTY + 8) * 8, 2); }
    STAMP0(2);

    gather576<200>(g_h, sm + SM_AVB, AV_PITCH, tid);
    cbar();
    STAMP0(3);
    mbar_wait(bars + BAR_WQ * 8, 0);
    {
        const int k = (mi >> 1) * 8 + r8;
        const uint32_t base = sm + SM_WQ + k * 64;
        const float4 r = gemv576x32(base + ((((mi & 1) * 2) ^ (r8 >> 1)) << 4), base + ((((mi & 1) * 2 + 1) ^ (r8 >> 1)) << 4), 1024,
                                    sm + SM_AVB, sm + SM_RED, warp, lane);
        if (warp == 0) {
            uint32_t* dst = reinterpret_cast<uint32_t*>(g_q) + cta * 64 + lane;
            pub32(dst, enc(pack_bf(r.x, r.y)));
            pub32(dst + 32, enc(pack_bf(r.z, r.w)));
            if (lane == 0) for (int i = 9; i < 12; i++) mbar_arrive_n(bars + (BAR_EMPTY + i) * 8, 2);
        }
    }
    STAMP0(4);
    if (tid >= 128) {
        uint4 v[1];
        poll<1, 100>(v, g_q + g * 128 + (tid - 128), 0);
        const uint4 u = unzip(v[0]);
        sts32(sm + SM_QS + (tid - 128) * 4, b == 0 ? u.x : b == 1 ? u.y : b == 2 ? u.z : u.w);
    }
    cbar();
    STAMP0(5);

    const int pr = warp >> 1, hf = warp & 1;
    {
        uint32_t qf[8][2];
#pragma unroll
        for (int ks = 0; ks < 8; ks++) {
            const uint32_t a = sm + SM_QS + ((lane >> 2) & 1) * 256 + ks * 32 + (lane & 3) * 4;
            qf[ks][0] = lds32(a); qf[ks][1] = lds32(a + 16);
        }
        const uint32_t koff = (hf * 32 + (mi & 1) * 8 + r8) * 128;
        uint32_t sw[4];
#pragma unroll
        for (int c = 0; c < 4; c++) sw[c] = koff + (((2 * c + (mi >> 1)) ^ r8) << 4);
#pragma unroll 1
        for (int i = pr; i < TILES; i += 4) {
            const int slot = i % NSLOT;
            mbar_wait(bars + (BAR_FULL + slot) * 8, (i / NSLOT) & 1);
            const uint32_t tb = sm + slot * TILE_BYTES;
            float c[4][4];
#pragma unroll
            for (int u = 0; u < 4; u++) { c[u][0] = c[u][1] = c[u][2] = c[u][3] = 0.f; }
#pragma unroll
            for (int ks = 0; ks < 4; ks++) {
#pragma unroll
                for (int u = 0; u < 4; u++) {
                    uint32_t a[4];
                    ldsm4(a, tb + (u >> 1) * 8192 + (u & 1) * 2048 + sw[ks]);
                    mma16816(c[u], a, qf[(u >> 1) * 4 + ks][0], qf[(u >> 1) * 4 + ks][1]);
                }
            }
            __syncwarp();
            if (lane == 0) mbar_arrive(bars + (BAR_EMPTY + slot) * 8);
            const bool t1 = (lane & 2) != 0, hi = (lane & 1) != 0;
            const float p0 = t1 ? (hi ? c[1][2] + c[3][2] : c[1][0] + c[3][0]) : (hi ? c[0][2] + c[2][2] : c[0][0] + c[2][0]);
            const float p1 = t1 ? (hi ? c[1][3] + c[3][3] : c[1][1] + c[3][1]) : (hi ? c[0][3] + c[2][3] : c[0][1] + c[2][1]);
            const uint32_t w = pack_bf(bfr(p0) * 0.08838834764831845f, bfr(p1) * 0.08838834764831845f);
            const uint32_t a = sm + SM_SC + (i * 64 + hf * 32 + (lane & 3) * 8 + (lane >> 2)) * 2;
            sts16(a, w & 0xFFFFu);
            sts16(a + 4096, w >> 16);
        }
    }
    cbar();
    STAMP0(6);

    float gab[4], gbb[4], xres[4];
    {
        const int head = tid >> 7;
        const uint32_t a = sm + SM_SC + tid * 32;
        const uint4 u0 = lds128(a), u1 = lds128(a + 16);
        const uint32_t w[8] = {u0.x, u0.y, u0.z, u0.w, u1.x, u1.y, u1.z, u1.w};
        float e[16];
        float m = -INFINITY;
#pragma unroll
        for (int i = 0; i < 8; i++) { e[2 * i] = bf_lo(w[i]); e[2 * i + 1] = bf_hi(w[i]); m = fmaxf(m, fmaxf(e[2 * i], e[2 * i + 1])); }
        m = warp_max(m);
        if (lane == 0) stsf(sm + SM_RED + warp * 4, m);
        cbar();
        const float4 mv = lds128f(sm + SM_RED + head * 16);
        m = fmaxf(fmaxf(mv.x, mv.y), fmaxf(mv.z, mv.w));
        float l = 0.f;
#pragma unroll
        for (int i = 0; i < 16; i++) { e[i] = exp2f((e[i] - m) * 1.4426950408889634f); l += e[i]; }
        l = warp_sum(l);
        if (lane == 0) stsf(sm + SM_RED + 32 + warp * 4, l);
        cbar();
        if (warp == 0) {
            if (lane < 2) {
                const float4 m0 = lds128f(sm + SM_RED), m1 = lds128f(sm + SM_RED + 16);
                const float4 l0 = lds128f(sm + SM_RED + 32), l1 = lds128f(sm + SM_RED + 48);
                const float ma = fmaxf(fmaxf(m0.x, m0.y), fmaxf(m0.z, m0.w)), mb = fmaxf(fmaxf(m1.x, m1.y), fmaxf(m1.z, m1.w));
                const float la = (l0.x + l0.y) + (l0.z + l0.w), lb = (l1.x + l1.y) + (l1.z + l1.w);
                pub128(g_stat + cta * 2 + lane, make_uint4(encf(ma), encf(la), encf(mb), encf(lb)));
                uint4 v[1];
                poll<1, 100>(v, g_stat + (cta ^ 1) * 2, 0);
                const float mm = lane ? mb : ma, ll = lane ? lb : la;
                const float mo = decf(lane ? v[0].z : v[0].x), lo = decf(lane ? v[0].w : v[0].y);
                const float mg = fmaxf(mm, mo);
                const float fm = exp2f((mm - mg) * 1.4426950408889634f), fo = exp2f((mo - mg) * 1.4426950408889634f);
                stsf(sm + SM_RED + 64 + lane * 4, __fdiv_rn(fm, s == 0 ? ll * fm + lo * fo : lo * fo + ll * fm));
            }
        } else if (warp <= 5) {
            const int t = tid - 32;
            if (t < 144) {
                uint4 v[4];
                poll<4, 100>(v, g_mod + 288 + t, 144);
#pragma unroll
                for (int i = 0; i < 4; i++) {
                    uint4 u = unzip(v[i]);
                    if (i >= 2) {
                        u.x = pack_bf(1.0f + bf_lo(u.x), 1.0f + bf_hi(u.x)); u.y = pack_bf(1.0f + bf_lo(u.y), 1.0f + bf_hi(u.y));
                        u.z = pack_bf(1.0f + bf_lo(u.z), 1.0f + bf_hi(u.z)); u.w = pack_bf(1.0f + bf_lo(u.w), 1.0f + bf_hi(u.w));
                    }
                    const uint32_t d = sm + (i >= 2 ? SM_CB1 : SM_SB) + (t + 144 * (i & 1)) * 4;
                    sts32(d, u.x); sts32(d + 1152, u.y); sts32(d + 2304, u.z); sts32(d + 3456, u.w);
                }
            }
        } else if (warp == 7 && cta < 72) {
            uint4 v[2];
            poll<2, 100>(v, g_mod + cta * 4 + ((lane & 7) >> 1), 864);
            const uint32_t a0 = ~((lane & 1) ? v[0].z : v[0].x), a1 = ~((lane & 1) ? v[0].w : v[0].y);
            const uint32_t b0 = ~((lane & 1) ? v[1].z : v[1].x), b1 = ~((lane & 1) ? v[1].w : v[1].y);
            gab[0] = bf_lo(a0); gab[1] = bf_hi(a0); gab[2] = bf_lo(a1); gab[3] = bf_hi(a1);
            gbb[0] = bf_lo(b0); gbb[1] = bf_hi(b0); gbb[2] = bf_lo(b1); gbb[3] = bf_hi(b1);
#pragma unroll
            for (int i = 0; i < 4; i++) xres[i] = __bfloat162float(x[i * D_MODEL + cta * 8 + (lane & 7)]);
        }
        cbar();
        const float f = ldsf(sm + SM_RED + 64 + head * 4);
        uint4 o0, o1;
        o0.x = pack_bf(e[0] * f, e[1] * f); o0.y = pack_bf(e[2] * f, e[3] * f); o0.z = pack_bf(e[4] * f, e[5] * f); o0.w = pack_bf(e[6] * f, e[7] * f);
        o1.x = pack_bf(e[8] * f, e[9] * f); o1.y = pack_bf(e[10] * f, e[11] * f); o1.z = pack_bf(e[12] * f, e[13] * f); o1.w = pack_bf(e[14] * f, e[15] * f);
        sts128(a, o0); sts128(a + 16, o1);
        cbar();
    }
    STAMP0(7);

    {
        float o[4][4];
#pragma unroll
        for (int u = 0; u < 4; u++) { o[u][0] = o[u][1] = o[u][2] = o[u][3] = 0.f; }
        const uint32_t voff = hf * 8192 + ((mi >> 1) * 8 + r8) * 128;
        uint32_t sw[4];
#pragma unroll
        for (int u = 0; u < 4; u++) sw[u] = voff + (((2 * u + (mi & 1)) ^ r8) << 4);
        const uint32_t pb = sm + SM_SC + ((lane >> 2) & 1) * 4096 + (lane & 3) * 4;
#pragma unroll 1
        for (int i = pr; i < TILES; i += 4) {
            const int it = i + TILES, slot = it % NSLOT;
            uint32_t pf[4][2];
#pragma unroll
            for (int kk = 0; kk < 4; kk++) { pf[kk][0] = lds32(pb + i * 128 + kk * 32); pf[kk][1] = lds32(pb + i * 128 + kk * 32 + 16); }
            mbar_wait(bars + (BAR_FULL + slot) * 8, (it / NSLOT) & 1);
            const uint32_t tb = sm + slot * TILE_BYTES;
#pragma unroll
            for (int kk = 0; kk < 4; kk++) {
#pragma unroll
                for (int u = 0; u < 4; u++) {
                    uint32_t a[4];
                    ldsm4t(a, tb + kk * 2048 + sw[u]);
                    mma16816(o[u], a, pf[kk][0], pf[kk][1]);
                }
            }
            __syncwarp();
            if (lane == 0) mbar_arrive(bars + (BAR_EMPTY + slot) * 8);
        }
        const int u = lane & 3;
        float v[4];
#pragma unroll
        for (int q = 0; q < 4; q++) v[q] = u == 0 ? o[0][q] : u == 1 ? o[1][q] : u == 2 ? o[2][q] : o[3][q];
        const uint32_t a = sm + SM_RED + pr * 1024 + (hf * 64 + u * 16 + (lane >> 2)) * 4;
        stsf(a, v[0]); stsf(a + 512, v[1]); stsf(a + 32, v[2]); stsf(a + 512 + 32, v[3]);
        cbar();
        STAMP0(8);
        const uint32_t r = sm + SM_RED + tid * 4;
        pub32(reinterpret_cast<uint32_t*>(g_opart) + cta * 256 + tid, encf((ldsf(r) + ldsf(r + 1024)) + (ldsf(r + 2048) + ldsf(r + 3072))));
    }

    {
        uint4 v[2];
        poll<2, 100>(v, g_opart + (g * 8 + (tid >> 6) * 2) * 64 + (tid & 63), 64);
        const uint32_t a = sm + SM_AVA + (tid >> 6) * AV_PITCH + (tid & 63) * 8;
        sts32(a, pack_bf(decf(v[0].x) + decf(v[1].x), decf(v[0].y) + decf(v[1].y)));
        sts32(a + 4, pack_bf(decf(v[0].z) + decf(v[1].z), decf(v[0].w) + decf(v[1].w)));
        cbar();
        STAMP0(9);
        if (warp < 5) {
            mbar_wait(bars + BAR_WO * 8, 0);
            const int blk = min(warp * 2 + (mi & 1), 8);
            const uint32_t ab = sm + SM_WO + ((mi >> 1) * 8 + r8) * 144 + blk * 16;
            const uint32_t bb = sm + SM_AVA + ((lane >> 2) & 3) * AV_PITCH + (lane & 3) * 4;
            float c[2][4] = {{0.f, 0.f, 0.f, 0.f}, {0.f, 0.f, 0.f, 0.f}};
#pragma unroll
            for (int ks = 0; ks < 16; ks++) {
                uint32_t a4[4];
                ldsm4t(a4, ab + ks * 2304);
                mma16816(c[ks & 1], a4, lds32(bb + ks * 32), lds32(bb + ks * 32 + 16));
            }
            const bool hi = (lane & 2) != 0;
            const int ob = warp * 2 + (hi ? 1 : 0);
            if (ob < 9)
                pub64(reinterpret_cast<uint2*>(g_wpart) + ((j * 9 + ob) * 16 + g) * 16 + (lane >> 2) * 2 + (lane & 1),
                      encf(hi ? c[0][2] + c[1][2] : c[0][0] + c[1][0]), encf(hi ? c[0][3] + c[1][3] : c[0][1] + c[1][1]));
            STAMP0(10);
        } else if (warp == 7 && cta < 72) {
            uint4 w[4];
            uint4* src = g_wpart + cta * 128 + lane;
            poll<4, 100>(w, src, 32);
            float t[4] = {0.f, 0.f, 0.f, 0.f};
#pragma unroll
            for (int i = 0; i < 4; i++) { t[0] += decf(w[i].x); t[1] += decf(w[i].y); t[2] += decf(w[i].z); t[3] += decf(w[i].w); }
#pragma unroll
            for (int q = 0; q < 4; q++) {
                t[q] += __shfl_xor_sync(0xffffffffu, t[q], 8);
                t[q] += __shfl_xor_sync(0xffffffffu, t[q], 16);
                xres[q] = bfr(xres[q] + bfr(gab[q] * bfr(t[q])));
            }
            if (lane < 8) pub64(reinterpret_cast<uint2*>(g_x1) + cta * 8 + lane, enc(pack_bf(xres[0], xres[1])), enc(pack_bf(xres[2], xres[3])));
#pragma unroll
            for (int i = 0; i < 4; i++) src[i * 32] = make_uint4(0, 0, 0, 0);
            if (lane == 0) STAMP(18);
        }
    }

    gather576<100>(g_x1, sm + SM_RED, 1152, tid);
    cbar();
    STAMP0(11);
    {
        const int bb = warp & 3, half = warp >> 2;
        uint32_t w[9];
#pragma unroll
        for (int i = 0; i < 9; i++) w[i] = lds32(sm + SM_RED + bb * 1152 + (lane + 32 * i) * 4);
        float mean_b, den_b;
        ln_stats(w, mean_b, den_b);
#pragma unroll
        for (int i = 0; i < 9; i++) {
            if ((i & 1) == half || (i == 8 && false)) {
                const uint32_t off = bb * 1152 + (lane + 32 * i) * 4;
                const uint32_t c1 = lds32(sm + SM_CB1 + off), sb = lds32(sm + SM_SB + off);
                const float h0 = bfr(ln_apply(bf_lo(w[i]), mean_b, den_b) * bf_lo(c1)) + bf_lo(sb);
                const float h1 = bfr(ln_apply(bf_hi(w[i]), mean_b, den_b) * bf_hi(c1)) + bf_hi(sb);
                sts32(sm + SM_AVB + bb * AV_PITCH + (lane + 32 * i) * 4, pack_bf(h0, h1));
            }
        }
        reinterpret_cast<uint32_t*>(g_opart)[cta * 256 + tid] = 0;
        if (tid < 64) reinterpret_cast<uint32_t*>(g_q)[cta * 64 + tid] = 0;
        else if (tid < 128) { if (cta >= 36 && cta < 108) reinterpret_cast<uint32_t*>(g_mod)[(cta - 36) * 64 + tid - 64] = 0; }
        else if (tid < 160) { if (cta < 36) reinterpret_cast<uint32_t*>(g_h)[cta * 32 + tid - 128] = 0; }
        else if (tid < 168) reinterpret_cast<uint32_t*>(g_stat)[cta * 8 + tid - 160] = 0;
    }
    cbar();

    mbar_wait(bars + BAR_WGU * 8, 0);
    STAMP0(12);
    {
        float c[5][4];
#pragma unroll
        for (int u = 0; u < 5; u++) { c[u][0] = c[u][1] = c[u][2] = c[u][3] = 0.f; }
        const uint32_t ab = sm + ((mi & 1) ? SM_WU : SM_WG) + ((mi >> 1) * 8 + r8) * 80;
        const uint32_t bb = sm + SM_AVB + ((lane >> 2) & 3) * AV_PITCH + (lane & 3) * 4;
#pragma unroll
        for (int i = 0; i < 5; i++) {
            const int ks = warp + 8 * i;
            if (ks < 36) {
                const uint32_t b0 = lds32(bb + ks * 32), b1 = lds32(bb + ks * 32 + 16);
#pragma unroll
                for (int u = 0; u < 5; u++) {
                    uint32_t a4[4];
                    ldsm4t(a4, ab + ks * 1280 + u * 16);
                    mma16816(c[u], a4, b0, b1);
                }
            }
        }
        const uint32_t rb = sm + SM_SC + warp * 1280 + ((lane >> 2) * 2 + (lane & 1)) * 16;
        if (lane & 2) {
            sts128f(rb + 256, c[1][0], c[1][1], c[1][2], c[1][3]);
            sts128f(rb + 768, c[3][0], c[3][1], c[3][2], c[3][3]);
        } else {
            sts128f(rb, c[0][0], c[0][1], c[0][2], c[0][3]);
            sts128f(rb + 512, c[2][0], c[2][1], c[2][2], c[2][3]);
            sts128f(rb + 1024, c[4][0], c[4][1], c[4][2], c[4][3]);
        }
        cbar();
        if (tid < 80) {
            float4 r = make_float4(0.f, 0.f, 0.f, 0.f);
#pragma unroll
            for (int w = 0; w < 8; w++) {
                const float4 v = lds128f(sm + SM_SC + w * 1280 + tid * 16);
                r.x += v.x; r.y += v.y; r.z += v.z; r.w += v.w;
            }
            const float g0 = bfr(r.x), g1 = bfr(r.y);
            const float e0 = bfr(0.5f * g0 * (1.0f + tanhf(0.7978845608028654f * (g0 + 0.044715f * g0 * g0 * g0))));
            const float e1 = bfr(0.5f * g1 * (1.0f + tanhf(0.7978845608028654f * (g1 + 0.044715f * g1 * g1 * g1))));
            const uint32_t w = pack_bf(e0 * bfr(r.z), e1 * bfr(r.w));
            const uint32_t a = sm + SM_AVA + (tid & 1) * 2 * AV_PITCH + (tid >> 1) * 2;
            sts16(a, w & 0xFFFFu);
            sts16(a + AV_PITCH, w >> 16);
        }
        cbar();
    }
    STAMP0(13);

    {
        const uint32_t bb = sm + SM_AVA + ((lane >> 2) & 3) * AV_PITCH + (lane & 3) * 4;
        uint32_t bf[5];
#pragma unroll
        for (int i = 0; i < 5; i++) bf[i] = lds32(bb + i * 16);
        mbar_wait(bars + BAR_WD * 8, 0);
        STAMP0(14);
        const uint32_t ab = sm + SM_WD + ((mi >> 1) * 8 + r8) * AV_PITCH + (mi & 1) * 16;
        const uint32_t ab2 = sm + SM_WD + (32 + r8) * AV_PITCH + (mi & 1) * 16;
        const bool hi = (lane & 2) != 0;
#pragma unroll
        for (int i = 0; i < 5; i++) {
            const int mt = warp + 8 * i;
            if (mt < 36) {
                float c[4] = {0.f, 0.f, 0.f, 0.f};
                uint32_t a4[4], a5[4];
                ldsm4t(a4, ab + mt * 32);
                ldsm4t(a5, ab + 16 * AV_PITCH + mt * 32);
                mma16816(c, a4, bf[0], bf[1]);
                mma16816(c, a5, bf[2], bf[3]);
                if (nblk == 5) {
                    uint32_t a2[2];
                    ldsm2t(a2, ab2 + mt * 32);
                    mma1688(c, a2, bf[4]);
                }
                pub64(reinterpret_cast<uint2*>(g_fpart) + ((2 * mt + (hi ? 1 : 0)) * NCTA + cta) * 16 + (lane >> 2) * 2 + (lane & 1),
                      encf(hi ? c[2] : c[0]), encf(hi ? c[3] : c[1]));
            }
        }
    }

    if (cta < 72) {
        uint4 w[4];
        uint4* src = g_fpart + cta * (NCTA * 8) + tid;
        poll<4, 0>(w, src, 256);
        float t[4] = {0.f, 0.f, 0.f, 0.f};
#pragma unroll
        for (int i = 0; i < 4; i++) { t[0] += decf(w[i].x); t[1] += decf(w[i].y); t[2] += decf(w[i].z); t[3] += decf(w[i].w); }
#pragma unroll
        for (int q = 0; q < 4; q++) {
            t[q] += __shfl_xor_sync(0xffffffffu, t[q], 8);
            t[q] += __shfl_xor_sync(0xffffffffu, t[q], 16);
        }
        if (lane < 8) sts128f(sm + SM_RED + 4096 + warp * 128 + lane * 16, t[0], t[1], t[2], t[3]);
#pragma unroll
        for (int i = 0; i < 4; i++) src[i * 256] = make_uint4(0, 0, 0, 0);
        cbar();
        if (warp == 7 && lane < 8) {
            float4 r = make_float4(0.f, 0.f, 0.f, 0.f);
#pragma unroll
            for (int w8 = 0; w8 < 8; w8++) {
                const float4 v = lds128f(sm + SM_RED + 4096 + w8 * 128 + lane * 16);
                r.x += v.x; r.y += v.y; r.z += v.z; r.w += v.w;
            }
            __nv_bfloat16* o = out + cta * 8 + lane;
            o[0] = __float2bfloat16_rn(xres[0] + bfr(gbb[0] * bfr(r.x)));
            o[D_MODEL] = __float2bfloat16_rn(xres[1] + bfr(gbb[1] * bfr(r.y)));
            o[2 * D_MODEL] = __float2bfloat16_rn(xres[2] + bfr(gbb[2] * bfr(r.z)));
            o[3 * D_MODEL] = __float2bfloat16_rn(xres[3] + bfr(gbb[3] * bfr(r.w)));
            reinterpret_cast<uint2*>(g_x1)[cta * 8 + lane] = make_uint2(0, 0);
        }
    }
    STAMP0(15);
}

typedef CUresult (*EncodeFn)(CUtensorMap*, CUtensorMapDataType, cuuint32_t, void*, const cuuint64_t*, const cuuint64_t*,
                             const cuuint32_t*, const cuuint32_t*, CUtensorMapInterleave, CUtensorMapSwizzle,
                             CUtensorMapL2promotion, CUtensorMapFloatOOBfill);

void make2d(EncodeFn enc_fn, CUtensorMap* m, const void* p, int rows, int cols, int box_cols, int box_rows, CUtensorMapSwizzle sw) {
    cuuint64_t gd[2] = {(cuuint64_t)cols, (cuuint64_t)rows};
    cuuint64_t gs[1] = {(cuuint64_t)cols * 2};
    cuuint32_t bx[2] = {(cuuint32_t)box_cols, (cuuint32_t)box_rows};
    cuuint32_t es[2] = {1, 1};
    enc_fn(m, CU_TENSOR_MAP_DATA_TYPE_BFLOAT16, 2, const_cast<void*>(p), gd, gs, bx, es, CU_TENSOR_MAP_INTERLEAVE_NONE, sw,
           CU_TENSOR_MAP_L2_PROMOTION_L2_128B, CU_TENSOR_MAP_FLOAT_OOB_FILL_NONE);
}
void makekv(EncodeFn enc_fn, CUtensorMap* m, const void* p) {
    cuuint64_t gd[3] = {64, (cuuint64_t)NB * 16 * SK, 2};
    cuuint64_t gs[2] = {256, 128};
    cuuint32_t bx[3] = {64, 64, 2};
    cuuint32_t es[3] = {1, 1, 1};
    enc_fn(m, CU_TENSOR_MAP_DATA_TYPE_BFLOAT16, 3, const_cast<void*>(p), gd, gs, bx, es, CU_TENSOR_MAP_INTERLEAVE_NONE,
           CU_TENSOR_MAP_SWIZZLE_128B, CU_TENSOR_MAP_L2_PROMOTION_L2_256B, CU_TENSOR_MAP_FLOAT_OOB_FILL_NONE);
}

}

extern "C" void kernel_launch(void* const* d_in, const int* in_sizes, int n_in, void* d_out, int out_size) {
    (void)in_sizes; (void)n_in; (void)out_size;
    EncodeFn enc_fn = nullptr;
    cudaDriverEntryPointQueryResult qr;
    cudaGetDriverEntryPoint("cuTensorMapEncodeTiled", (void**)&enc_fn, cudaEnableDefault, &qr);
    cudaFuncSetAttribute(fused_block_kernel, cudaFuncAttributeMaxDynamicSharedMemorySize, SM_TOTAL);
    Maps maps;
    makekv(enc_fn, &maps.k, d_in[1]);
    makekv(enc_fn, &maps.v, d_in[2]);
    make2d(enc_fn, &maps.wmod16, d_in[10], D_MODEL, 6 * D_MODEL, 16, 192, CU_TENSOR_MAP_SWIZZLE_32B);
    make2d(enc_fn, &maps.wmod32, d_in[10], D_MODEL, 6 * D_MODEL, 32, 192, CU_TENSOR_MAP_SWIZZLE_64B);
    make2d(enc_fn, &maps.wq, d_in[3], D_MODEL, 4096, 32, 192, CU_TENSOR_MAP_SWIZZLE_64B);
    make2d(enc_fn, &maps.wo, d_in[4], 4096, D_MODEL, 72, 128, CU_TENSOR_MAP_SWIZZLE_NONE);
    make2d(enc_fn, &maps.wg, d_in[6], D_MODEL, FF, 40, 192, CU_TENSOR_MAP_SWIZZLE_NONE);
    make2d(enc_fn, &maps.wu, d_in[7], D_MODEL, FF, 40, 192, CU_TENSOR_MAP_SWIZZLE_NONE);
    fused_block_kernel<<<NCTA, NTHREADS, SM_TOTAL>>>(maps, (const __nv_bfloat16*)d_in[0], (const __nv_bfloat16*)d_in[9],
                                                     (const __nv_bfloat16*)d_in[8], (__nv_bfloat16*)d_out);
}
```

```cpp
#include <cuda_runtime.h>
#include <cuda_bf16.h>
#include <cuda.h>
#include <stdint.h>
#include <stdlib.h>

namespace {

constexpr int D_MODEL = 576;
constexpr int NB = 4;
constexpr int SK = 4096;
constexpr int FF = 4608;
constexpr int NCTA = 128;
constexpr int NTHREADS = 320;
constexpr int NSLOT = 12;
constexpr int TILE_BYTES = 16384;
constexpr int TILES = 32;
constexpr int AV_PITCH = 1168;

constexpr int SM_W0 = 7 * TILE_BYTES;
constexpr int SM_X = 4 * TILE_BYTES;
constexpr int SM_WO = SM_X + 36864;
constexpr int SM_WG = SM_WO + 32768;
constexpr int SM_WD = 12288;
constexpr int SM_GRED = 3 * TILE_BYTES;
constexpr int SM_SC = NSLOT * TILE_BYTES;
constexpr int SM_RED = SM_SC + 8192;
constexpr int SM_AVA = SM_RED + 4096;
constexpr int SM_AVB = SM_AVA + 4 * AV_PITCH;
constexpr int SM_CB1 = SM_AVB + 4 * AV_PITCH;
constexpr int SM_SB = SM_CB1 + 4 * AV_PITCH;
constexpr int SM_QS = SM_SB + 4 * AV_PITCH;
constexpr int SM_XR = SM_QS + 512;
constexpr int SM_BAR = SM_XR + 64;
constexpr int CH_KV = 6, CH_WO = 70, CH_GA = 76, CH_GB = 88, CH_WD = 94, NCHUNK = 100;
constexpr int REL = NCHUNK, RELW = REL + 64, NBAR = RELW + 2;
constexpr int SM_TAB = SM_BAR + 1344;
static_assert(NBAR * 8 <= 1344, "bars");
constexpr int SM_ADJ = SM_TAB + NCHUNK * 16;
constexpr int SM_ORG = SM_ADJ + 16;
constexpr int SM_TOTAL = SM_ORG + 96;
static_assert(SM_TOTAL <= 232448, "smem");
#define NB_ 1
constexpr int NBURST = NB_;
__host__ __device__ constexpr int slot_of(int i) { return i < 48 ? i % NSLOT : ((i - 48) % 6 < 4 ? (i - 48) % 6 : (i - 48) % 6 + 6); }

#define EVF 2
#define NHARD 4
#define HARD_WAIT 0x546
#define WQ_FREE 0
#define KVPROMO CU_TENSOR_MAP_L2_PROMOTION_L2_256B
#define SLP 40
#define SLP_GATE 200
#define GATE_MASK 15
#define SLP_R 0
#define SLP_G 0
#define SLP_O 0
#define GATE_ACT false

constexpr unsigned SPIN_LIMIT = 1u << 22;
constexpr float LOG2E = 1.4426950408889634f;

enum { M_K = 0, M_V, M_WMOD, M_WQ, M_WO, M_WD, M_WG, M_WU, M_WOX, M_WDX, M_WGX, M_WUX, NMAPS };
struct alignas(16) Plan { uint32_t e[128][4]; };
struct Params { CUtensorMap m[NMAPS]; int pace; };

constexpr int knob(const char*, int dflt) { return dflt; }
#define PLAN_CONST constexpr

PLAN_CONST Plan make_plan() {
    Plan pl = {};
    const int early_from = knob("EARLY_FROM", 56), early_n = knob("EARLY_N", 0), main_from = knob("MAIN_FROM", 18);
    const int win_start = knob("WIN_START", 48), win_main = knob("WIN_MAIN", 64), win_last = knob("WIN_LAST", 64), n_last = knob("N_LAST", 0);
    const int win_wo = knob("WIN_WO", 32), win_gu = knob("WIN_GU", 32), win_wd = knob("WIN_WD", 32);
    const int step_main = knob("STEP_MAIN", 16), step_tail = knob("STEP_TAIL", 6);
    const unsigned char tail[30] = {70, 74, 71, 75, 72, 73, 76, 77, 84, 85, 78, 79, 80, 81, 86, 87, 82, 83,
                                           88, 89, 92, 93, 90, 91, 94, 95, 96, 97, 98, 99};
    int order[NCHUNK] = {}, n = 0, w = 0, last_tile = 0;
    for (int i = 0; i < 3; i++) order[n++] = i;
    for (int i = 0; i < NBURST; i++) order[n++] = CH_KV + i;
    for (int i = 3; i < 6; i++) order[n++] = i;
    for (int i = NBURST; i < 2 * TILES; i++) {
        last_tile = n;
        order[n++] = CH_KV + i;
        if (i >= early_from && i < 2 * TILES - 1 && w < early_n) order[n++] = tail[w++];
    }
    while (w < 30) order[n++] = tail[w++];
    int last_user[NSLOT] = {};
    for (int i = 0; i < NSLOT; i++) last_user[i] = i >= 9 ? RELW + 1 : i >= 7 ? RELW : 0;
    int bytes_at[NCHUNK] = {};
    bool seen[256] = {};
    for (int p = 0; p < NCHUNK; p++) {
        const int c = order[p];
        const int x = c == 74 || c == 75 ? c - 74 : c >= 84 && c < 88 ? c - 82 : c == 92 || c == 93 ? c - 86 : -1;
        int map = 0, dst = 0, row = 0, bytes = 0;
        if (c < CH_KV) { map = c < 3 ? M_WMOD : M_WQ; dst = SM_W0 + c * 12288; bytes = 12288; row = (c % 3) * 192; }
        else if (c < CH_WO) { const int i = c - CH_KV; map = i / TILES; dst = slot_of(i) * TILE_BYTES; bytes = TILE_BYTES; row = (i % TILES) * 128; }
        else if (x >= 0) { map = 0; dst = SM_X; bytes = 0; row = x; }
        else if (c < CH_GA) { const int t = c - CH_WO; map = M_WO; dst = SM_WO + t * 8192; bytes = 8192; row = t * 64; }
        else if (c < CH_WD) { const int t = c < CH_GB ? c - CH_GA : c - CH_GB + 8; map = M_WG + (t & 1); dst = t < 10 ? SM_WG + t * 6144 : (t - 10) * 6144; bytes = 6144; row = (t >> 1) * 96; }
        else { const int t = c - CH_WD; map = M_WD; dst = SM_WD + t * 6144; bytes = 6144; row = t * 48; }
        bytes_at[p] = bytes ? bytes : 2048;
        unsigned rel = 0, wait = 0;
        if (x >= 0) rel = 0;
        else if (c == CH_WO - 1 - 8) rel = last_user[dst / TILE_BYTES] | (last_user[4] << 8);
        else if (c == CH_WO - 1 - 9) rel = last_user[dst / TILE_BYTES] | (last_user[5] << 8);
        else if (c >= CH_KV) rel = last_user[dst / TILE_BYTES] | (last_user[(dst + bytes - 1) / TILE_BYTES] << 8);
        if (c >= CH_KV && c < CH_WO) last_user[dst / TILE_BYTES] = REL + c - CH_KV;
        for (int k = 0; k < 16; k += 8) {
            const unsigned r = (rel >> k) & 255;
            if (seen[r]) rel &= ~(255u << k);
            seen[r] = true;
        }
        if (!(rel & 255)) rel >>= 8;
        const int win = p < main_from ? win_start : p <= last_tile - n_last ? win_main : p <= last_tile ? win_last
                      : c < CH_GA ? win_wo : c < CH_WD ? win_gu : win_wd;
        const int step = p < main_from ? 0 : p > last_tile ? step_tail : step_main;
        for (int k = 0; k < 4; k++) {
            const int lim = (win + (k - 1) * step) * 1024;
            int q = p - 1, sum = bytes_at[p];
            while (q > 0 && (sum + bytes_at[q] <= lim || bytes_at[q] == 2048)) sum += bytes_at[q--];
            wait |= (unsigned)order[q < 0 ? 0 : q] << (8 * k);
        }
        pl.e[p][0] = dst | (map << 20) | (c << 24); pl.e[p][1] = row | (bytes << 16); pl.e[p][2] = rel; pl.e[p][3] = wait;
    }
    return pl;
}
__device__ const Plan g_plan = make_plan();

constexpr int NREP = 16;
constexpr int G_CNT = 0;
constexpr int G_H = G_CNT + 8;
constexpr int G_MOD = G_H + NREP * 288;
constexpr int G_Q = G_MOD + 1152;
constexpr int G_STAT = G_Q + 2048;
constexpr int G_OPART = G_STAT + NCTA * 2;
constexpr int G_X1 = G_OPART + NCTA * 64;
constexpr int G_ACT = G_X1 + NREP * 288;
constexpr int G_PART = G_ACT + 2304;
constexpr int G_TOTAL = G_PART + 2 * 72 * 128;
__device__ __align__(128) uint4 g_scr[G_TOTAL];
#define STAMP(i)
#define STAMPT(t, i)
#define STAMP0(i)
constexpr int SM_LAUNCH = SM_TOTAL;

__device__ __forceinline__ uint32_t enc(uint32_t w) { return max(~w, 1u); }
__device__ __forceinline__ uint32_t encf(float f) { return enc(__float_as_uint(f)); }
__device__ __forceinline__ float decf(uint32_t w) { return __uint_as_float(~w); }
__device__ __forceinline__ float bf_lo(uint32_t w) { return __uint_as_float(w << 16); }
__device__ __forceinline__ float bf_hi(uint32_t w) { return __uint_as_float(w & 0xFFFF0000u); }
__device__ __forceinline__ uint32_t pack_bf(float lo, float hi) {
    uint32_t r;
    asm("cvt.rn.bf16x2.f32 %0, %1, %2;" : "=r"(r) : "f"(hi), "f"(lo));
    return r;
}
__device__ __forceinline__ float bfr(float x) { return __uint_as_float(pack_bf(0.f, x)); }
__device__ __forceinline__ uint32_t mul2(uint32_t a, uint32_t b) { uint32_t r; asm("mul.rn.bf16x2 %0, %1, %2;" : "=r"(r) : "r"(a), "r"(b)); return r; }
__device__ __forceinline__ uint32_t add2(uint32_t a, uint32_t b) { uint32_t r; asm("add.rn.bf16x2 %0, %1, %2;" : "=r"(r) : "r"(a), "r"(b)); return r; }
__device__ __forceinline__ uint32_t sub2(uint32_t a, uint32_t b) { uint32_t r; asm("sub.rn.bf16x2 %0, %1, %2;" : "=r"(r) : "r"(a), "r"(b)); return r; }
__device__ __forceinline__ float ex2(float x) { float r; asm("ex2.approx.ftz.f32 %0, %1;" : "=f"(r) : "f"(x)); return r; }
__device__ __forceinline__ float rcp(float x) { float r; asm("rcp.approx.ftz.f32 %0, %1;" : "=f"(r) : "f"(x)); return r; }
__device__ __forceinline__ float fsqrt(float x) { float r; asm("sqrt.approx.ftz.f32 %0, %1;" : "=f"(r) : "f"(x)); return r; }
__device__ __forceinline__ float sigm(float x) { return rcp(1.0f + ex2(-LOG2E * x)); }
__device__ __forceinline__ void mbar_init(uint32_t bar, uint32_t cnt) {
    asm volatile("mbarrier.init.shared::cta.b64 [%0], %1;" ::"r"(bar), "r"(cnt) : "memory");
}
__device__ __forceinline__ void mbar_expect(uint32_t bar, uint32_t bytes) {
    asm volatile("mbarrier.arrive.expect_tx.shared::cta.b64 _, [%0], %1;" ::"r"(bar), "r"(bytes) : "memory");
}
__device__ __forceinline__ void mbar_arrive(uint32_t bar) {
    asm volatile("mbarrier.arrive.shared::cta.b64 _, [%0];" ::"r"(bar) : "memory");
}
__device__ __forceinline__ void mbar_wait(uint32_t bar) {
    asm volatile("{\n.reg .pred p;\n.reg .u32 n;\nmov.u32 n, 0;\n"
                 "W_%=:\nmbarrier.try_wait.parity.shared::cta.b64 p, [%0], 0;\n@p bra D_%=;\n"
                 "add.u32 n, n, 1;\nsetp.lt.u32 p, n, %1;\n@p bra W_%=;\ntrap;\nD_%=:\n}"
                 ::"r"(bar), "n"(SPIN_LIMIT) : "memory");
}
__device__ __forceinline__ bool mbar_test(uint32_t bar) {
    uint32_t ok;
    asm volatile("{\n.reg .pred p;\nmbarrier.test_wait.parity.shared::cta.b64 p, [%1], 0;\nselp.u32 %0, 1, 0, p;\n}" : "=r"(ok) : "r"(bar) : "memory");
    return ok != 0;
}
__device__ __forceinline__ void tma3(uint32_t dst, const CUtensorMap* m, int c0, int c1, int c2, uint32_t bar, uint64_t pol) {
    asm volatile("cp.async.bulk.tensor.3d.shared::cluster.global.mbarrier::complete_tx::bytes.L2::cache_hint [%0], [%1, {%3, %4, %5}], [%2], %6;"
                 ::"r"(dst), "l"(m), "r"(bar), "r"(c0), "r"(c1), "r"(c2), "l"(pol) : "memory");
}
__device__ __forceinline__ void cbar() { asm volatile("bar.sync 1, 256;" ::: "memory"); }
__device__ __forceinline__ void ldsm4(uint32_t (&r)[4], uint32_t a) {
    asm volatile("ldmatrix.sync.aligned.m8n8.x4.shared.b16 {%0,%1,%2,%3}, [%4];"
                 : "=r"(r[0]), "=r"(r[1]), "=r"(r[2]), "=r"(r[3]) : "r"(a) : "memory");
}
__device__ __forceinline__ void ldsm4t(uint32_t (&r)[4], uint32_t a) {
    asm volatile("ldmatrix.sync.aligned.m8n8.x4.trans.shared.b16 {%0,%1,%2,%3}, [%4];"
                 : "=r"(r[0]), "=r"(r[1]), "=r"(r[2]), "=r"(r[3]) : "r"(a) : "memory");
}
__device__ __forceinline__ void mma16816(float (&c)[4], const uint32_t (&a)[4], uint32_t b0, uint32_t b1) {
    asm volatile("mma.sync.aligned.m16n8k16.row.col.f32.bf16.bf16.f32 {%0,%1,%2,%3}, {%4,%5,%6,%7}, {%8,%9}, {%0,%1,%2,%3};"
                 : "+f"(c[0]), "+f"(c[1]), "+f"(c[2]), "+f"(c[3])
                 : "r"(a[0]), "r"(a[1]), "r"(a[2]), "r"(a[3]), "r"(b0), "r"(b1));
}
__device__ __forceinline__ uint32_t lds32(uint32_t a) {
    uint32_t r; asm volatile("ld.shared.b32 %0, [%1];" : "=r"(r) : "r"(a) : "memory"); return r;
}
__device__ __forceinline__ uint32_t lds16(uint32_t a) {
    unsigned short r; asm volatile("ld.shared.b16 %0, [%1];" : "=h"(r) : "r"(a) : "memory"); return r;
}
__device__ __forceinline__ float ldsf(uint32_t a) { return __uint_as_float(lds32(a)); }
__device__ __forceinline__ uint4 lds128(uint32_t a) {
    uint4 r; asm volatile("ld.shared.v4.b32 {%0,%1,%2,%3}, [%4];" : "=r"(r.x), "=r"(r.y), "=r"(r.z), "=r"(r.w) : "r"(a) : "memory"); return r;
}
__device__ __forceinline__ float4 lds128f(uint32_t a) {
    float4 r; asm volatile("ld.shared.v4.f32 {%0,%1,%2,%3}, [%4];" : "=f"(r.x), "=f"(r.y), "=f"(r.z), "=f"(r.w) : "r"(a) : "memory"); return r;
}
__device__ __forceinline__ void sts16(uint32_t a, uint32_t v) { asm volatile("st.shared.b16 [%0], %1;" ::"r"(a), "h"((unsigned short)v) : "memory"); }
__device__ __forceinline__ void sts32(uint32_t a, uint32_t v) { asm volatile("st.shared.b32 [%0], %1;" ::"r"(a), "r"(v) : "memory"); }
__device__ __forceinline__ void sts64(uint32_t a, uint32_t x, uint32_t y) { asm volatile("st.shared.v2.b32 [%0], {%1,%2};" ::"r"(a), "r"(x), "r"(y) : "memory"); }
__device__ __forceinline__ void stsf(uint32_t a, float v) { sts32(a, __float_as_uint(v)); }
__device__ __forceinline__ void sts128(uint32_t a, uint4 v) {
    asm volatile("st.shared.v4.b32 [%0], {%1,%2,%3,%4};" ::"r"(a), "r"(v.x), "r"(v.y), "r"(v.z), "r"(v.w) : "memory");
}
__device__ __forceinline__ void sts128f(uint32_t a, float x, float y, float z, float w) {
    asm volatile("st.shared.v4.f32 [%0], {%1,%2,%3,%4};" ::"r"(a), "f"(x), "f"(y), "f"(z), "f"(w) : "memory");
}
__device__ __forceinline__ float4 sum8(uint32_t a, int st) {
    float4 v[8];
#pragma unroll
    for (int w = 0; w < 8; w++) v[w] = lds128f(a + w * st);
#pragma unroll
    for (int o = 4; o; o >>= 1)
#pragma unroll
        for (int w = 0; w < o; w++) { v[w].x += v[w + o].x; v[w].y += v[w + o].y; v[w].z += v[w + o].z; v[w].w += v[w + o].w; }
    return v[0];
}
__device__ __forceinline__ void pub32(bool p, void* a, uint32_t v) {
    asm volatile("{\n.reg .pred q;\nsetp.ne.u32 q, %2, 0;\n@q st.relaxed.gpu.global.b32 [%0], %1;\n}" ::"l"(a), "r"(v), "r"((uint32_t)p) : "memory");
}
__device__ __forceinline__ void pub64(bool p, void* a, uint32_t x, uint32_t y) {
    asm volatile("{\n.reg .pred q;\nsetp.ne.u32 q, %3, 0;\n@q st.relaxed.gpu.global.v2.b32 [%0], {%1,%2};\n}" ::"l"(a), "r"(x), "r"(y), "r"((uint32_t)p) : "memory");
}
__device__ __forceinline__ void st16(bool p, void* a, uint32_t v) {
    asm volatile("{\n.reg .pred q;\nsetp.ne.u32 q, %2, 0;\n@q st.global.b16 [%0], %1;\n}" ::"l"(a), "h"((unsigned short)v), "r"((uint32_t)p) : "memory");
}
__device__ __forceinline__ void clr128(bool p, void* a) {
    asm volatile("{\n.reg .pred q;\nsetp.ne.u32 q, %1, 0;\n@q st.relaxed.gpu.global.v4.b32 [%0], {%2,%2,%2,%2};\n}" ::"l"(a), "r"((uint32_t)p), "r"(0) : "memory");
}
__device__ __forceinline__ void ldg_missing(uint4& r, const uint4* p, uint32_t lo) {
    asm volatile("{\n.reg .pred q;\nsetp.eq.u32 q, %5, 0;\n@q ld.relaxed.gpu.global.v4.b32 {%0,%1,%2,%3}, [%4];\n}"
                 : "+r"(r.x), "+r"(r.y), "+r"(r.z), "+r"(r.w) : "l"(p), "r"(lo) : "memory");
}
__device__ __forceinline__ uint32_t min4(const uint4& v) { return min(min(v.x, v.y), min(v.z, v.w)); }
template <int N, int SLEEP, bool GATE>
__device__ __forceinline__ void poll(uint4 (&v)[N], const uint4* p, int stride) {
    uint32_t lo[N];
#pragma unroll
    for (int i = 0; i < N; i++) { v[i] = make_uint4(0, 0, 0, 0); lo[i] = 0; }
    unsigned it = 0;
    if (GATE) {
#pragma unroll 1
        do {
            if (SLP_GATE && it) __nanosleep(SLP_GATE);
            ldg_missing(v[0], p, threadIdx.x & GATE_MASK);
            lo[0] = min4(v[0]);
            if (++it > SPIN_LIMIT) __trap();
        } while (!__any_sync(0xffffffffu, lo[0] != 0));
    }
#pragma unroll 1
    for (;;) {
#pragma unroll
        for (int i = 0; i < N; i++) ldg_missing(v[i], p + i * stride, lo[i]);
        uint32_t all = 0xFFFFFFFFu;
#pragma unroll
        for (int i = 0; i < N; i++) { lo[i] = min4(v[i]); all = min(all, lo[i]); }
        if (__all_sync(0xffffffffu, all != 0)) break;
        if (++it > SPIN_LIMIT) __trap();
        if (SLEEP) __nanosleep(SLEEP);
    }
}
__device__ __forceinline__ uint4 unzip(const uint4& e) {
    uint4 r;
    r.x = ~__byte_perm(e.x, e.z, 0x5410);
    r.y = ~__byte_perm(e.x, e.z, 0x7632);
    r.z = ~__byte_perm(e.y, e.w, 0x5410);
    r.w = ~__byte_perm(e.y, e.w, 0x7632);
    return r;
}
template <int N, bool GATE>
__device__ __forceinline__ void gather(const uint4* src, uint32_t dst, int pitch, int tid) {
    uint4 v[N];
    const int t = min(tid, 143);
    poll<N, SLP_G, GATE>(v, src + t, 144);
#pragma unroll
    for (int i = 0; i < N; i++) {
        const uint4 u = unzip(v[i]);
        const uint32_t a = dst + (t + 144 * i) * 4;
        sts32(a, u.x); sts32(a + pitch, u.y); sts32(a + 2 * pitch, u.z); sts32(a + 3 * pitch, u.w);
    }
}
__device__ __forceinline__ float ln_rden(float var) { return rcp(bfr(fsqrt(bfr(bfr(fmaxf(var, 0.f)) + 1e-5f)))); }
__device__ __forceinline__ void ln_stats(const uint32_t (&w)[9], float& mean_b, float& rden) {
    const float piv = __shfl_sync(0xffffffffu, bf_lo(w[0]), 0);
    float s = 0.f, q = 0.f;
#pragma unroll
    for (int i = 0; i < 9; i++) {
        const float a = bf_lo(w[i]) - piv, c = bf_hi(w[i]) - piv;
        s += a + c;
        q = fmaf(a, a, fmaf(c, c, q));
    }
#pragma unroll
    for (int o = 16; o; o >>= 1) { s += __shfl_xor_sync(0xffffffffu, s, o); q += __shfl_xor_sync(0xffffffffu, q, o); }
    s *= (1.0f / D_MODEL);
    mean_b = bfr(piv + s);
    rden = ln_rden(fmaf(q, 1.0f / D_MODEL, -s * s));
}
__device__ __forceinline__ float ln_mod(float x, float mean_b, float rden, float scale1, float shift) {
    return bfr(bfr(bfr(x - mean_b) * rden) * scale1) + shift;
}

__device__ __forceinline__ uint32_t ln_mod2(uint32_t x, uint32_t mean2, float rden, uint32_t scale1, uint32_t shift) {
    const uint32_t d = sub2(x, mean2);
    return add2(mul2(pack_bf(bf_lo(d) * rden, bf_hi(d) * rden), scale1), shift);
}
__device__ __forceinline__ bool landed(uint32_t bars, int first, int n, int lane) {
    return __all_sync(0xffffffffu, mbar_test(bars + (first + min(lane, n - 1)) * 8));
}
__device__ __forceinline__ void wait_landed(uint32_t bars, int first, int n, int lane) {
    if (lane < n) mbar_wait(bars + (first + lane) * 8);
    __syncwarp();
}

__global__ void __launch_bounds__(NTHREADS, 1)
fused_block_kernel(const __grid_constant__ Params prm, const __nv_bfloat16* __restrict__ x, const __nv_bfloat16* __restrict__ cvec,
                   __nv_bfloat16* __restrict__ out, uint4* __restrict__ scr, const void* __restrict__ plan) {
    extern __shared__ __align__(1024) unsigned char smem_raw[];
    const uint32_t sm = (uint32_t)__cvta_generic_to_shared(smem_raw);
    const uint32_t bars = sm + SM_BAR;
    const int tid = threadIdx.x, warp = __shfl_sync(0xffffffffu, tid >> 5, 0), lane = tid & 31;
    const int cta = blockIdx.x;
    const int g = cta >> 3, j = cta & 7, b = j >> 1, s = j & 1;
    const int f0 = g * 288 + j * 32, fx = g * 288 + 192 + j * 16;
    const bool xg = (j >> 1) == 2;

    const int row0 = (b * 16 + g) * SK + s * 64;
    if (warp >= 8) {
    if (warp == 8) {
        uint64_t pol_kv, pol_w;
        asm volatile("createpolicy.fractional.L2::evict_first.b64 %0, 1.0;" : "=l"(pol_kv));
        asm volatile("createpolicy.fractional.L2::evict_normal.b64 %0, 1.0;" : "=l"(pol_w));
        if (!EVF) pol_kv = pol_w;
        if (EVF == 2) pol_w = pol_kv;
        if (lane == 0) {
#pragma unroll
            for (int n = 0; n < 12; n++) mbar_init(bars + n * 8, 1);
            mbar_init(bars + RELW * 8, 1);
            mbar_init(bars + (RELW + 1) * 8, 1);
            asm volatile("fence.mbarrier_init.release.cluster;" ::: "memory");
#pragma unroll
            for (int n = 0; n < 3; n++) {
                mbar_expect(bars + n * 8, cta < 108 ? 12288 : 0);
                if (cta < 108) tma3(sm + SM_W0 + n * 12288, &prm.m[M_WMOD], (cta % 36) * 16, n * 192, (cta / 36) * 2, bars + n * 8, pol_w);
            }
#pragma unroll
            for (int n = 0; n < NBURST; n++) {
                mbar_expect(bars + (CH_KV + n) * 8, TILE_BYTES);
                tma3(sm + n * TILE_BYTES, &prm.m[M_K], 0, row0 + n * 128, 0, bars + (CH_KV + n) * 8, pol_kv);
            }
        }
        __syncwarp();
        asm volatile("bar.arrive 4, %0;" ::"n"(NTHREADS) : "memory");
        if (lane == 0) {
#pragma unroll 1
            for (int n = 0; n < 3; n++) {
                mbar_expect(bars + (3 + n) * 8, 12288);
                if (n >= WQ_FREE) mbar_wait(bars + (n - WQ_FREE) * 8);
                tma3(sm + SM_W0 + (3 + n) * 12288, &prm.m[M_WQ], cta * 32, n * 192, 0, bars + (3 + n) * 8, pol_w);
            }
#pragma unroll 1
            for (int n = NBURST; n < NHARD; n++) {
                mbar_expect(bars + (CH_KV + n) * 8, TILE_BYTES);
                mbar_wait(bars + ((HARD_WAIT >> (4 * (n - NBURST))) & 15) * 8);
                tma3(sm + n * TILE_BYTES, &prm.m[M_K], 0, row0 + n * 128, 0, bars + (CH_KV + n) * 8, pol_kv);
            }
        }
        __syncwarp();
        asm volatile("bar.sync 2, 64;" ::: "memory");
        if (lane == 0) {
            if (sm & 1023) __trap();
            STAMP(46);
            uint4 e = lds128(sm + SM_TAB + (6 + NHARD) * 16);
#pragma unroll 1
            for (int p = 6 + NHARD; p < NCHUNK; p++) {
                const uint32_t adj = lds32(sm + SM_ADJ);
                const uint4 nx = lds128(sm + SM_TAB + (p + 1) * 16);
                if (e.x & 0x80000u) {
                    if (e.y >> 16) {
                        mbar_wait(bars + ((e.y >> 16) & 255) * 8);
                        if (e.y >> 24) mbar_wait(bars + (e.y >> 24) * 8);
                    }
                    mbar_wait(bars + ((e.w >> adj) & 255) * 8);
                    tma3(sm + (e.x & 0x7FFFF), &prm.m[(e.x >> 20) & 15], e.y & 0xFFFF, e.z, 0, bars + (e.x >> 24) * 8,
                         (e.x & 0xE00000u) ? pol_w : pol_kv);
                }
                e = nx;
            }
        }
    } else if (warp == 9) {
        if (lane < NMAPS)
            sts64(sm + SM_ORG + lane * 8,
                  lane <= M_V ? 0 : lane <= M_WQ ? cta * 32 : lane <= M_WD ? j * 64 : lane <= M_WU ? f0 : lane <= M_WDX ? 512 + j * 16 : fx,
                  lane <= M_V ? row0 : (lane & 2) ? 0 : (lane & 1) ? g * 288 : g * 256);
        if (lane == 0) sts32(sm + SM_ADJ, 8);
        uint4 pe[4];
#pragma unroll
        for (int i = 0; i < 4; i++) pe[i] = __ldg(reinterpret_cast<const uint4*>(plan) + lane + 32 * i);
        asm volatile("bar.sync 4, %0;" ::"n"(NTHREADS) : "memory");
#pragma unroll
        for (int i = 0; i < 4; i++) {
            if ((pe[i].y >> 16) == 0) {
                const uint32_t t = pe[i].y, h = t & 1;
                pe[i].x += xg ? h * 18432 + ((t >> 1) - 1) * 6144 + ((M_WGX + h) << 20)
                              : t < 2 ? h * 4096 + (M_WOX << 20) : 8192 + h * 4608 + (M_WDX << 20);
                pe[i].y = xg ? (t < 2 ? 0 : ((t >> 1) - 1) * 192 + (6144 << 16))
                             : j >= 4 ? 0 : t < 2 ? h * 128 + (4096 << 16) : t >= 6 ? h * 144 + (4608 << 16) : 0;
            }
            const int p = lane + 32 * i;
            if (p < NCHUNK) {
                const uint32_t org = sm + SM_ORG + ((pe[i].x >> 20) & 15) * 8;
                if (p >= 6 + NHARD) mbar_expect(bars + (pe[i].x >> 24) * 8, pe[i].y >> 16);
                sts128(sm + SM_TAB + p * 16, make_uint4(pe[i].x | ((pe[i].y >> 16) ? 0x80000u : 0u), lds32(org) | (pe[i].z << 16),
                                                        lds32(org + 4) + (pe[i].y & 0xFFFF), pe[i].w));
            }
        }
        asm volatile("bar.arrive 2, 64;" ::: "memory");
        __syncwarp();
        if (lane == 0) {
            int done = 0;
#pragma unroll 1
            while (done < NCHUNK) {
                int n = done;
                mbar_wait(bars + (lds32(sm + SM_TAB + n * 16) >> 24) * 8);
                while (++n < NCHUNK && mbar_test(bars + (lds32(sm + SM_TAB + n * 16) >> 24) * 8)) {}
                const unsigned add = (n == NCHUNK ? 128 : n) - done;
                const int all = (atomicAdd(reinterpret_cast<unsigned*>(scr + G_CNT), add) & 16383u) + (n - done);
                const int lead = n * NCTA - all;
                sts32(sm + SM_ADJ, lead > prm.pace ? 0 : lead < -2 * prm.pace ? 24 : lead < -prm.pace ? 16 : 8);
                done = n;
            }
        }
    }
    } else {
    uint2 cw[3];
    uint32_t xw[9];
#pragma unroll
    for (int i = 0; i < 3; i++) cw[i] = cta < 108 ? __ldg(reinterpret_cast<const uint2*>(cvec) + min(tid + 256 * i, 575)) : make_uint2(0, 0);
#pragma unroll
    for (int i = 0; i < 9; i++) xw[i] = cta < 36 && warp >= 4 ? __ldg(reinterpret_cast<const uint32_t*>(x) + (warp & 3) * 288 + lane + 32 * i) : 0u;
    if (lane == 0) {
        static_assert(NCHUNK == 12 + 88, "11 chunk barriers and 8 release barriers per warp");
#pragma unroll
        for (int n = 0; n < 11; n++) mbar_init(bars + (12 + warp * 11 + n) * 8, 1);
#pragma unroll
        for (int n = 0; n < 8; n++) mbar_init(bars + (REL + warp * 8 + n) * 8, 2);
        asm volatile("fence.mbarrier_init.release.cluster;" ::: "memory");
    }
    asm volatile("bar.sync 4, %0;" ::"n"(NTHREADS) : "memory");
    const int mi = lane >> 3, r8 = lane & 7;
    const uint32_t bfrag = ((lane >> 2) & 3) * AV_PITCH + (lane & 3) * 4;
    uint32_t* const scr32 = reinterpret_cast<uint32_t*>(scr);
    uint2* const scr64 = reinterpret_cast<uint2*>(scr);
    const int pr = warp >> 1, hf = warp & 1;

#pragma unroll
    for (int i = 0; i < 3; i++) {
        const int p = min(tid + 256 * i, 575);
        const float a0 = bf_lo(cw[i].x), a1 = bf_hi(cw[i].x), a2 = bf_lo(cw[i].y), a3 = bf_hi(cw[i].y);
        sts64(sm + SM_AVA + (p / 144) * AV_PITCH + (p % 144) * 8, pack_bf(a0 * sigm(a0), a1 * sigm(a1)), pack_bf(a2 * sigm(a2), a3 * sigm(a3)));
    }
    if (cta < 36 && warp >= 4) {
        float mean_b, rden;
        ln_stats(xw, mean_b, rden);
        if (lane == 0) sts64(sm + SM_QS + (warp & 3) * 8, __float_as_uint(mean_b), __float_as_uint(rden));
#pragma unroll
        for (int i = 0; i < 9; i++) sts32(sm + SM_CB1 + (warp & 3) * 1152 + (lane + 32 * i) * 4, xw[i]);
    }
#pragma unroll 1
    for (int it = 0; it < 2; it++) {
        if (it == 1 && tid < 160) gather<2, true>(scr + (G_H + g * 288), sm + SM_AVB, AV_PITCH, tid);
        cbar();
        if (cta < 108 || it == 1) {
            STAMP0(1 + 2 * it);
            const int k = (mi >> 1) * 8 + r8;
            const uint32_t base = sm + SM_W0 + (it ? 36864 + k * 64 : (mi & 1) * 6144 + k * 32);
            const uint32_t ch = it ? (((mi & 1) * 2) ^ (r8 >> 1)) : (r8 >> 2);
            const uint32_t a0 = base + (ch << 4), a1 = base + ((ch ^ 1) << 4), kb = it ? 1024 : 512;
            const uint32_t bb = sm + (it ? SM_AVB : SM_AVA) + bfrag + warp * 32;
            float c0[4] = {0.f, 0.f, 0.f, 0.f}, c1[4] = {0.f, 0.f, 0.f, 0.f};
            uint32_t bq[5][2];
#pragma unroll
            for (int i = 0; i < 5; i++) { bq[i][0] = lds32(bb + i * 256); bq[i][1] = lds32(bb + i * 256 + 16); }
            if (warp >= 4) bq[4][0] = bq[4][1] = 0;
#pragma unroll
            for (int i = 0; i < 3; i++) mbar_wait(bars + (it * 3 + i) * 8);
#pragma unroll
            for (int i = 0; i < 5; i++) {
                const int ks = min(warp + 8 * i, 35);
                const int cq = ks / 12;
                const uint32_t off = cq * 12288 + (ks - cq * 12) * kb;
                uint32_t u[4], v[4];
                ldsm4t(u, a0 + off);
                ldsm4t(v, a1 + off);
                mma16816(c0, u, bq[i][0], bq[i][1]);
                mma16816(c1, v, bq[i][0], bq[i][1]);
            }
            const bool t1 = (lane & 2) != 0;
            sts128f(sm + SM_RED + warp * 512 + (t1 ? 256 : 0) + ((lane >> 2) * 2 + (lane & 1)) * 16,
                    t1 ? c1[0] : c0[0], t1 ? c1[1] : c0[1], t1 ? c1[2] : c0[2], t1 ? c1[3] : c0[3]);
            cbar();
            if (warp == 7) {
                const float4 r = sum8(sm + SM_RED + lane * 16, 512);
                if (it == 0 && cta < 36) {
                    const uint32_t xp = sm + SM_CB1 + (lane & 1) * 2304 + (cta * 16 + (lane >> 1)) * 2;
                    const float4 st = lds128f(sm + SM_QS + (lane & 1) * 16);
                    const float h0 = ln_mod(bf_lo(lds16(xp)), st.x, st.y, bfr(1.0f + bfr(r.z)), bfr(r.x));
                    const float h1 = ln_mod(bf_lo(lds16(xp + 1152)), st.z, st.w, bfr(1.0f + bfr(r.w)), bfr(r.y));
                    const uint32_t hv = enc(pack_bf(h0, h1));
#pragma unroll
                    for (int i = 0; i < NREP; i++) pub32(true, scr32 + (G_H * 4 + i * 1152 + cta * 32 + lane), hv);
                } else {
                    uint32_t* dst = scr32 + ((it ? G_Q * 4 + cta * 64 : G_MOD * 4 + ((cta / 72) * 1152 + (cta % 36) * 16) * 2) + lane);
                    pub32(true, dst, enc(pack_bf(r.x, r.y)));
                    pub32(true, dst + (it ? 32 : 1152), enc(pack_bf(r.z, r.w)));
                }
            }
        }
        if (tid == 192) mbar_arrive(bars + (RELW + it) * 8);
    }

    if (tid < 128) {
        uint4 v[1];
        poll<1, SLP, false>(v, scr + (G_Q + g * 128 + tid), 0);
        const uint4 u = unzip(v[0]);
        sts32(sm + SM_QS + tid * 4, b == 0 ? u.x : b == 1 ? u.y : b == 2 ? u.z : u.w);
    }
    cbar();
    STAMP0(5);
    {
        uint32_t qf[8][2];
#pragma unroll
        for (int ks = 0; ks < 8; ks++) {
            const uint32_t a = sm + SM_QS + ((lane >> 2) & 1) * 256 + ks * 32 + (lane & 3) * 4;
            qf[ks][0] = lds32(a); qf[ks][1] = lds32(a + 16);
        }
        const uint32_t koff = (hf * 32 + (mi & 1) * 8 + r8) * 128;
        uint32_t sw[4];
#pragma unroll
        for (int c = 0; c < 4; c++) sw[c] = koff + (((2 * c + (mi >> 1)) ^ r8) << 4);
#pragma unroll 1
        for (int i = pr; i < TILES; i += 4) {
            mbar_wait(bars + (CH_KV + i) * 8);
            const uint32_t tb = sm + (i % NSLOT) * TILE_BYTES;
            float c[4][4];
#pragma unroll
            for (int u = 0; u < 4; u++) { c[u][0] = c[u][1] = c[u][2] = c[u][3] = 0.f; }
#pragma unroll
            for (int ks = 0; ks < 4; ks++) {
#pragma unroll
                for (int u = 0; u < 4; u++) {
                    uint32_t a[4];
                    ldsm4(a, tb + (u >> 1) * 8192 + (u & 1) * 2048 + sw[ks]);
                    mma16816(c[u], a, qf[(u >> 1) * 4 + ks][0], qf[(u >> 1) * 4 + ks][1]);
                }
            }
            __syncwarp();
            if (lane == 0) mbar_arrive(bars + (REL + i) * 8);
            const bool t1 = (lane & 2) != 0, hi = (lane & 1) != 0;
            const float p0 = t1 ? (hi ? c[1][2] + c[3][2] : c[1][0] + c[3][0]) : (hi ? c[0][2] + c[2][2] : c[0][0] + c[2][0]);
            const float p1 = t1 ? (hi ? c[1][3] + c[3][3] : c[1][1] + c[3][1]) : (hi ? c[0][3] + c[2][3] : c[0][1] + c[2][1]);
            const uint32_t w = pack_bf(bfr(p0) * 0.08838834764831845f, bfr(p1) * 0.08838834764831845f);
            const uint32_t a = sm + SM_SC + (i * 64 + hf * 32 + (lane & 3) * 8 + (lane >> 2)) * 2;
            sts16(a, w & 0xFFFFu);
            sts16(a + 4096, w >> 16);
        }
    }
    cbar();
    STAMP0(6);

    {
        const uint32_t a = sm + SM_SC + tid * 32;
        const uint4 u0 = lds128(a), u1 = lds128(a + 16);
        const uint32_t w[8] = {u0.x, u0.y, u0.z, u0.w, u1.x, u1.y, u1.z, u1.w};
        float e[16], m = -INFINITY;
#pragma unroll
        for (int i = 0; i < 8; i++) { e[2 * i] = bf_lo(w[i]); e[2 * i + 1] = bf_hi(w[i]); m = fmaxf(m, fmaxf(e[2 * i], e[2 * i + 1])); }
#pragma unroll
        for (int o = 16; o; o >>= 1) m = fmaxf(m, __shfl_xor_sync(0xffffffffu, m, o));
        float l = 0.f;
#pragma unroll
        for (int i = 0; i < 16; i++) { e[i] = ex2((e[i] - m) * LOG2E); l += e[i]; }
#pragma unroll
        for (int o = 16; o; o >>= 1) l += __shfl_xor_sync(0xffffffffu, l, o);
        if (lane == 0) { stsf(sm + SM_RED + warp * 4, m); stsf(sm + SM_RED + 32 + warp * 4, l); }
        cbar();
        if (warp == 5) {
            const float4 m4 = lds128f(sm + SM_RED + (lane & 1) * 16), l4 = lds128f(sm + SM_RED + 32 + (lane & 1) * 16);
            const float mm = fmaxf(fmaxf(m4.x, m4.y), fmaxf(m4.z, m4.w));
            const float ll = (l4.x * ex2((m4.x - mm) * LOG2E) + l4.y * ex2((m4.y - mm) * LOG2E)) +
                             (l4.z * ex2((m4.z - mm) * LOG2E) + l4.w * ex2((m4.w - mm) * LOG2E));
            pub64(lane < 4, scr64 + (G_STAT * 2 + cta * 4 + lane), encf(mm), encf(ll));
            uint4 v[1];
            poll<1, SLP, false>(v, scr + (G_STAT + (cta ^ 1) * 2), 0);
            const float mo = decf((lane & 1) ? v[0].z : v[0].x), lo = decf((lane & 1) ? v[0].w : v[0].y);
            const float mg = fmaxf(mm, mo);
            sts64(sm + SM_RED + 64 + (lane & 1) * 8, __float_as_uint(mg),
                  __float_as_uint(rcp(ll * ex2((mm - mg) * LOG2E) + lo * ex2((mo - mg) * LOG2E))));
        } else if (warp < 5) {
            const int t = min(tid, 143);
            uint4 v[4];
            poll<4, SLP, false>(v, scr + (G_MOD + 288 + t), 144);
#pragma unroll
            for (int i = 0; i < 4; i++) {
                uint4 u = unzip(v[i]);
                if (i >= 2) {
                    u.x = pack_bf(1.0f + bf_lo(u.x), 1.0f + bf_hi(u.x)); u.y = pack_bf(1.0f + bf_lo(u.y), 1.0f + bf_hi(u.y));
                    u.z = pack_bf(1.0f + bf_lo(u.z), 1.0f + bf_hi(u.z)); u.w = pack_bf(1.0f + bf_lo(u.w), 1.0f + bf_hi(u.w));
                }
                const uint32_t d = sm + (i >= 2 ? SM_CB1 : SM_SB) + (t + 144 * (i & 1)) * 4;
                sts32(d, u.x); sts32(d + AV_PITCH, u.y); sts32(d + 2 * AV_PITCH, u.z); sts32(d + 3 * AV_PITCH, u.w);
            }
        } else if (warp == 6) {
            clr128(lane < (xg ? 24 : 16), scr + (G_ACT + (lane < 16 ? f0 / 2 + lane : fx / 2 + lane - 16)));
            __threadfence();
        } else if (cta < 72) {
            sts16(sm + SM_XR + (lane & 7) * 8 + (lane >> 3) * 2,
                  reinterpret_cast<const unsigned short*>(x)[(lane >> 3) * D_MODEL + cta * 8 + (lane & 7)]);
            uint4 v[2];
            poll<2, SLP, false>(v, scr + (G_MOD + cta * 4 + ((lane & 7) >> 1)), 864);
            sts128(sm + SM_QS + (lane & 7) * 16, make_uint4(~((lane & 1) ? v[0].z : v[0].x), ~((lane & 1) ? v[0].w : v[0].y),
                                                            ~((lane & 1) ? v[1].z : v[1].x), ~((lane & 1) ? v[1].w : v[1].y)));
        }
        cbar();
        const uint32_t st = sm + SM_RED + 64 + (tid >> 7) * 8;
        const float f = ex2((m - ldsf(st)) * LOG2E) * ldsf(st + 4);
        uint4 o0, o1;
        o0.x = pack_bf(e[0] * f, e[1] * f); o0.y = pack_bf(e[2] * f, e[3] * f); o0.z = pack_bf(e[4] * f, e[5] * f); o0.w = pack_bf(e[6] * f, e[7] * f);
        o1.x = pack_bf(e[8] * f, e[9] * f); o1.y = pack_bf(e[10] * f, e[11] * f); o1.z = pack_bf(e[12] * f, e[13] * f); o1.w = pack_bf(e[14] * f, e[15] * f);
        sts128(a, o0); sts128(a + 16, o1);
        cbar();
    }
    STAMP0(7);

    uint32_t wa[2][18][4];
    const bool pw = warp < 4 || (warp == 4 && j < 4);
    const uint32_t astep = warp < 4 ? 2048 : 512;
    const uint32_t aoff = warp < 4 ? ((mi >> 1) * 8 + r8) * 128 + (((warp * 2 + (mi & 1)) ^ r8) << 4)
                                   : ((mi >> 1) * 8 + r8) * 32 + (((mi & 1) ^ (r8 >> 2)) << 4);
    const uint32_t abase[2] = {sm + (warp < 4 ? SM_WO : SM_X) + aoff, sm + (warp < 4 ? SM_WD : SM_X + 8192) + aoff};
    bool have0 = false, have1 = false;
    {
        float o[4][4];
#pragma unroll
        for (int u = 0; u < 4; u++) { o[u][0] = o[u][1] = o[u][2] = o[u][3] = 0.f; }
        const uint32_t voff = hf * 8192 + ((mi >> 1) * 8 + r8) * 128;
        uint32_t sw[4];
#pragma unroll
        for (int u = 0; u < 4; u++) sw[u] = voff + (((2 * u + (mi & 1)) ^ r8) << 4);
        const uint32_t pb = sm + SM_SC + ((lane >> 2) & 1) * 4096 + (lane & 3) * 4 - TILES * 128;
        auto v_tile = [&](int i) {
            uint32_t pf[4][2];
#pragma unroll
            for (int kk = 0; kk < 4; kk++) { pf[kk][0] = lds32(pb + i * 128 + kk * 32); pf[kk][1] = lds32(pb + i * 128 + kk * 32 + 16); }
            const uint32_t tb = sm + slot_of(i) * TILE_BYTES;
            mbar_wait(bars + (CH_KV + i) * 8);
#pragma unroll
            for (int kk = 0; kk < 4; kk++) {
#pragma unroll
                for (int u = 0; u < 4; u++) {
                    uint32_t a[4];
                    ldsm4t(a, tb + kk * 2048 + sw[u]);
                    mma16816(o[u], a, pf[kk][0], pf[kk][1]);
                }
            }
            __syncwarp();
            if (lane == 0) mbar_arrive(bars + (REL + i) * 8);
        };
#pragma unroll 1
        for (int i = TILES + pr; i < 2 * TILES - 4; i += 4) v_tile(i);
        if (pw) {
            have0 = have1 = landed(bars, CH_WO, 6, lane);
            if (have0) {
#pragma unroll
                for (int u = 0; u < 16; u++) ldsm4t(wa[0][u], abase[0] + u * astep);
            }
        }
        v_tile(2 * TILES - 4 + pr);
        const int u = lane & 3;
        float v[4];
#pragma unroll
        for (int q = 0; q < 4; q++) v[q] = u == 0 ? o[0][q] : u == 1 ? o[1][q] : u == 2 ? o[2][q] : o[3][q];
        const uint32_t a = sm + SM_RED + pr * 1024 + (hf * 64 + u * 16 + (lane >> 2)) * 4;
        stsf(a, v[0]); stsf(a + 512, v[1]); stsf(a + 32, v[2]); stsf(a + 512 + 32, v[3]);
    }
    cbar();
    {
        const uint32_t r = sm + SM_RED + tid * 4;
        pub32(true, scr32 + (G_OPART * 4 + cta * 256 + tid), encf((ldsf(r) + ldsf(r + 1024)) + (ldsf(r + 2048) + ldsf(r + 3072))));
        STAMPT(0, 8);
        uint4 v[2];
        poll<2, SLP_O, false>(v, scr + (G_OPART + (g * 8 + (tid >> 6) * 2) * 64 + (tid & 63)), 64);
        sts64(sm + SM_AVA + (tid >> 6) * AV_PITCH + (tid & 63) * 8,
              pack_bf(decf(v[0].x) + decf(v[1].x), decf(v[0].y) + decf(v[1].y)),
              pack_bf(decf(v[0].z) + decf(v[1].z), decf(v[0].w) + decf(v[1].w)));
    }

#pragma unroll
    for (int rd = 0; rd < 2; rd++) {
        const uint32_t ab = abase[rd];
        const int ch0 = warp == 4 ? (rd ? CH_GB + 4 : CH_WO + 4) : rd ? CH_WD : CH_WO, n0 = warp == 4 ? 2 : 3 + rd;
        const int ch1 = warp == 4 ? ch0 : ch0 + n0;
        STAMPT(0, 34 + rd);
        if (rd == 0) cbar(); else if (warp < 5) asm volatile("bar.sync 3, 160;" ::: "memory");
        STAMP0(9 + 5 * rd);
        if (pw) {
            uint32_t b4[9][4];
#pragma unroll
            for (int u = 0; u < 8 + rd; u++) ldsm4(b4[u], sm + SM_AVA + (r8 & 3) * AV_PITCH + mi * 16 + u * 64);
            float c[4][4];
#pragma unroll
            for (int u = 0; u < 4; u++) { c[u][0] = c[u][1] = c[u][2] = c[u][3] = 0.f; }
            if (!have0) {
                wait_landed(bars, ch0, n0, lane);
#pragma unroll
                for (int u = 0; u < 12; u++) ldsm4t(wa[rd][u], ab + u * astep);
            }
#pragma unroll
            for (int u = 0; u < 12; u++) mma16816(c[u & 3], wa[rd][u], b4[u >> 1][(u & 1) * 2], b4[u >> 1][(u & 1) * 2 + 1]);
            if (!have1) {
                wait_landed(bars, ch1, 1 + rd, lane);
#pragma unroll
                for (int u = 12; u < 16 + 2 * rd; u++) ldsm4t(wa[rd][u], ab + u * astep);
            }
#pragma unroll
            for (int u = 12; u < 16 + 2 * rd; u++) mma16816(c[u & 3], wa[rd][u], b4[u >> 1][(u & 1) * 2], b4[u >> 1][(u & 1) * 2 + 1]);
            const bool hi = (lane & 2) != 0;
            const int ob = (warp < 4 ? j * 8 + warp * 2 : 64 + j * 2) + (hi ? 1 : 0);
            pub64(true, scr64 + ((G_PART + rd * 72 * 128 + (ob * 16 + g) * 8) * 2 + (lane >> 2) * 2 + (lane & 1)),
                  encf(hi ? (c[2][2] + c[3][2]) + (c[0][2] + c[1][2]) : (c[2][0] + c[3][0]) + (c[0][0] + c[1][0])),
                  encf(hi ? (c[2][3] + c[3][3]) + (c[0][3] + c[1][3]) : (c[2][1] + c[3][1]) + (c[0][1] + c[1][1])));
            STAMPT(0, 10 + 5 * rd);
        } else if (warp == 7 && cta < 72) {
            const uint32_t g01 = lds32(sm + SM_QS + (lane & 7) * 16 + rd * 8), g23 = lds32(sm + SM_QS + (lane & 7) * 16 + rd * 8 + 4);
            const uint32_t r01 = lds32(sm + SM_XR + (lane & 7) * 8), r23 = lds32(sm + SM_XR + 4 + (lane & 7) * 8);
            uint4 w[4];
            uint4* src = scr + (G_PART + rd * 72 * 128 + cta * 128 + lane);
            poll<4, SLP_R, false>(w, src, 32);
            STAMPT(224, 36 + rd);
            float t[4] = {(decf(w[0].x) + decf(w[1].x)) + (decf(w[2].x) + decf(w[3].x)), (decf(w[0].y) + decf(w[1].y)) + (decf(w[2].y) + decf(w[3].y)),
                          (decf(w[0].z) + decf(w[1].z)) + (decf(w[2].z) + decf(w[3].z)), (decf(w[0].w) + decf(w[1].w)) + (decf(w[2].w) + decf(w[3].w))};
#pragma unroll
            for (int q = 0; q < 4; q++) t[q] += __shfl_xor_sync(0xffffffffu, t[q], 8);
#pragma unroll
            for (int q = 0; q < 4; q++) t[q] += __shfl_xor_sync(0xffffffffu, t[q], 16);
            const uint32_t x01 = add2(r01, mul2(g01, pack_bf(t[0], t[1]))), x23 = add2(r23, mul2(g23, pack_bf(t[2], t[3])));
            if (rd == 1) {
                const uint32_t ov = (lane & 16) ? x23 : x01;
                st16(true, out + ((lane >> 3) * D_MODEL + cta * 8 + (lane & 7)), (lane & 8) ? ov >> 16 : ov);
            }
#pragma unroll
            for (int i = 0; i < NREP / 4; i++)
                pub64(true, scr64 + (G_X1 * 2 + (i * 4 + (lane >> 3)) * 576 + cta * 8 + (lane & 7)), rd ? 0u : enc(x01), rd ? 0u : enc(x23));
            STAMPT(224, 18 + rd);
            if (rd == 0) sts64(sm + SM_XR + (lane & 7) * 8, x01, x23);
#pragma unroll
            for (int i = 0; i < 4; i++) clr128(true, src + i * 32);
        }
        if (rd == 1) break;

        uint32_t wg[5][6][4];
        const bool four = warp >= 4;
        auto load_gu = [&](int i0, int i1) {
#pragma unroll
            for (int i = i0; i < i1; i++) {
                if (i < 4 || !four) {
                    const int ks = warp + 8 * i, rc = ks / 6, k = ks * 16 + (mi >> 1) * 8 + r8;
                    const uint32_t ag = sm + (rc < 5 ? SM_WG + rc * 6144 : -30720) + (mi & 1) * 6144 + k * 64;
#pragma unroll
                    for (int u = 0; u < 4; u++) ldsm4t(wg[i][u], ag + ((u ^ (r8 >> 1)) << 4));
                    if (xg) {
#pragma unroll
                        for (int u = 0; u < 2; u++) ldsm4t(wg[i][4 + u], sm + SM_X + (mi & 1) * 18432 + k * 32 + ((u ^ (r8 >> 2)) << 4));
                    }
                }
            }
        };
        auto mma_gu = [&](float (&c)[6][4], const uint32_t (&bq)[5][2], int i0, int i1) {
#pragma unroll
            for (int i = i0; i < i1; i++) {
                if (i < 4 || !four) {
#pragma unroll
                    for (int u = 0; u < 4; u++) mma16816(c[u], wg[i][u], bq[i][0], bq[i][1]);
                    if (xg) { mma16816(c[4], wg[i][4], bq[i][0], bq[i][1]); mma16816(c[5], wg[i][5], bq[i][0], bq[i][1]); }
                }
            }
        };
        have0 = landed(bars, CH_GA, 12, lane);
        if (have0) load_gu(0, 3);
        STAMPT(0, 38);
        if (tid < 160) gather<2, true>(scr + (G_X1 + g * 288), sm + SM_AVB, AV_PITCH, tid);
        STAMPT(0, 39);
        cbar();
        STAMP0(11);
        uint32_t bq[5][2];
        {
            const uint32_t fo = bfrag + warp * 32;
#pragma unroll
            for (int i = 0; i < 5; i++) { bq[i][0] = lds32(sm + SM_AVB + fo + i * 256); bq[i][1] = lds32(sm + SM_AVB + fo + i * 256 + 16); }
            const uint32_t piv2 = lane < 16 ? 0u : __byte_perm(lds32(sm + SM_AVB + ((lane >> 2) & 3) * AV_PITCH), 0, 0x1010);
            float m0[4] = {0.f, 0.f, 0.f, 0.f}, m1[4] = {0.f, 0.f, 0.f, 0.f};
#pragma unroll
            for (int i = 0; i < 5; i++) {
                uint32_t d[4] = {sub2(bq[i][0], piv2), 0x3F803F80u, sub2(bq[i][1], piv2), 0x3F803F80u};
                if (i == 4 && four) d[0] = d[2] = 0;
                mma16816((i & 1) ? m1 : m0, d, d[0], d[2]);
            }
            if ((lane & 3) == (lane >> 3))
                sts64(sm + SM_RED + (lane >> 2) * 80 + warp * 8, __float_as_uint((lane & 4) ? m0[3] + m1[3] : m0[2] + m1[2]),
                      __float_as_uint((lane & 4) ? m0[1] + m1[1] : m0[0] + m1[0]));
            have1 = landed(bars, CH_GB, 6, lane);
            cbar();
            const uint32_t ra = sm + SM_RED + (lane >> 2) * 80;
            const float4 p0 = lds128f(ra), p1 = lds128f(ra + 16), p2 = lds128f(ra + 32), p3 = lds128f(ra + 48);
            const float sd = (((p0.x + p0.z) + (p1.x + p1.z)) + ((p2.x + p2.z) + (p3.x + p3.z))) * (1.0f / D_MODEL);
            const float sq = ((p0.y + p0.w) + (p1.y + p1.w)) + ((p2.y + p2.w) + (p3.y + p3.w));
            float mean = bf_hi(piv2) + sd, var = fmaf(sq, 1.0f / D_MODEL, -sd * sd);
            const float mean_o = __shfl_xor_sync(0xffffffffu, mean, 16), var_o = __shfl_xor_sync(0xffffffffu, var, 16);
            uint32_t c1[5][2], sb[5][2];
#pragma unroll
            for (int i = 0; i < 5; i++) {
                c1[i][0] = lds32(sm + SM_CB1 + fo + i * 256); c1[i][1] = lds32(sm + SM_CB1 + fo + i * 256 + 16);
                sb[i][0] = lds32(sm + SM_SB + fo + i * 256); sb[i][1] = lds32(sm + SM_SB + fo + i * 256 + 16);
            }
            const float mean_r = lane < 16 ? mean : mean_o, var_r = lane < 16 ? var : var_o;
            if ((mean_r * mean_r > 16.0f * var_r) == (lane < 16)) { mean = mean_o; var = var_o; }
            const float mean_b = bfr(mean), rden = ln_rden(var);
            STAMPT(0, 40);
            const uint32_t mean2 = __byte_perm(__float_as_uint(mean_b), 0, 0x3232);
#pragma unroll
            for (int i = 0; i < 5; i++) {
                bq[i][0] = ln_mod2(bq[i][0], mean2, rden, c1[i][0], sb[i][0]);
                bq[i][1] = ln_mod2(bq[i][1], mean2, rden, c1[i][1], sb[i][1]);
            }
        }
        STAMPT(0, 12);
        {
            float c[6][4];
#pragma unroll
            for (int u = 0; u < 6; u++) { c[u][0] = c[u][1] = c[u][2] = c[u][3] = 0.f; }
            if (!have0) { wait_landed(bars, CH_GA, 12, lane); load_gu(0, 3); }
            if (have1) load_gu(3, 5);
            mma_gu(c, bq, 0, 3);
            STAMPT(0, 42);
            if (!have1) { wait_landed(bars, CH_GB, 6, lane); load_gu(3, 5); }
            mma_gu(c, bq, 3, 5);
            STAMPT(0, 43);
            const bool t1 = (lane & 2) != 0;
            const uint32_t rb = sm + SM_GRED + warp * 1536 + (t1 ? 256 : 0) + ((lane >> 2) * 2 + (lane & 1)) * 16;
#pragma unroll
            for (int u = 0; u < 6; u += 2)
                sts128f(rb + u * 256, t1 ? c[u + 1][0] : c[u][0], t1 ? c[u + 1][1] : c[u][1], t1 ? c[u + 1][2] : c[u][2], t1 ? c[u + 1][3] : c[u][3]);
        }
        STAMPT(0, 44);
        if (tid >= 160) {
            cbar();
            const int t = tid - 160;
            const float4 r = sum8(sm + SM_GRED + t * 16, 1536);
            const float g0 = bfr(r.x), g1 = bfr(r.y);
            const float e0 = g0 * sigm(1.5957691216057308f * (g0 + 0.044715f * g0 * g0 * g0));
            const float e1 = g1 * sigm(1.5957691216057308f * (g1 + 0.044715f * g1 * g1 * g1));
            pub32(t < 64 || xg, scr32 + (G_ACT * 4 + (t < 64 ? f0 * 2 + t : fx * 2 + t - 64)), enc(mul2(pack_bf(e0, e1), pack_bf(r.z, r.w))));
            STAMPT(160, 13);
            int z = G_OPART + cta * 64 + t;
            if (t >= 64) z = G_Q + cta * 16 + t - 64;
            if (t >= 80) z = G_MOD + (cta / 72) * 576 + (cta % 36) * 8 + (t & 7) + ((t & 8) ? 288 : 0);
            clr128(t < 80 || (cta >= 36 && cta < 108), scr + z);
            clr128(t < 38, scr + (t < 36 ? G_H + cta * 36 + t : G_STAT + cta * 2 + t - 36));
        } else {
            asm volatile("bar.arrive 1, 256;" ::: "memory");
            have0 = landed(bars, warp < 4 ? CH_WD : CH_GB + 2, 4, lane);
            if (have0) {
#pragma unroll
                for (int u = 0; u < 12; u++) ldsm4t(wa[1][u], abase[1] + u * astep);
            }
            have1 = landed(bars, warp < 4 ? CH_WD + 4 : CH_GB + 4, 2, lane);
            if (have1) {
#pragma unroll
                for (int u = 12; u < 18; u++) ldsm4t(wa[1][u], abase[1] + u * astep);
            }
            STAMPT(0, 33);
            gather<1, GATE_ACT>(scr + (G_ACT + g * 144), sm + SM_AVA, AV_PITCH, tid);
        }
    }
    }
}

typedef CUresult (*EncodeFn)(CUtensorMap*, CUtensorMapDataType, cuuint32_t, void*, const cuuint64_t*, const cuuint64_t*,
                             const cuuint32_t*, const cuuint32_t*, CUtensorMapInterleave, CUtensorMapSwizzle,
                             CUtensorMapL2promotion, CUtensorMapFloatOOBfill);

void make3d(EncodeFn fn, CUtensorMap* m, const void* p, uint64_t d0, uint64_t d1, uint64_t d2, uint64_t s1, uint64_t s2,
            uint32_t b0, uint32_t b1, uint32_t b2, CUtensorMapSwizzle sw, CUtensorMapL2promotion promo) {
    cuuint64_t gd[3] = {d0, d1, d2};
    cuuint64_t gs[2] = {s1, s2};
    cuuint32_t bx[3] = {b0, b1, b2};
    cuuint32_t es[3] = {1, 1, 1};
    fn(m, CU_TENSOR_MAP_DATA_TYPE_BFLOAT16, 3, const_cast<void*>(p), gd, gs, bx, es, CU_TENSOR_MAP_INTERLEAVE_NONE, sw, promo,
       CU_TENSOR_MAP_FLOAT_OOB_FILL_NONE);
}

}

extern "C" void kernel_launch(void* const* d_in, const int* in_sizes, int n_in, void* d_out, int out_size) {
    (void)in_sizes; (void)n_in; (void)out_size;
    EncodeFn fn = nullptr;
    cudaDriverEntryPointQueryResult qr;
    cudaGetDriverEntryPoint("cuTensorMapEncodeTiled", (void**)&fn, cudaEnableDefault, &qr);
    cudaFuncSetAttribute(fused_block_kernel, cudaFuncAttributeMaxDynamicSharedMemorySize, SM_LAUNCH);
    Params prm;
    prm.pace = knob("PACE", 64);
#define WPROMO CU_TENSOR_MAP_L2_PROMOTION_L2_128B
    const CUtensorMapL2promotion P128 = WPROMO, P256 = KVPROMO;
    make3d(fn, &prm.m[M_K], d_in[1], 64, (uint64_t)NB * 16 * SK, 2, 256, 128, 64, 64, 2, CU_TENSOR_MAP_SWIZZLE_128B, P256);
    make3d(fn, &prm.m[M_V], d_in[2], 64, (uint64_t)NB * 16 * SK, 2, 256, 128, 64, 64, 2, CU_TENSOR_MAP_SWIZZLE_128B, P256);
    make3d(fn, &prm.m[M_WMOD], d_in[10], D_MODEL, D_MODEL, 6, 6 * D_MODEL * 2, D_MODEL * 2, 16, 192, 2, CU_TENSOR_MAP_SWIZZLE_32B, P128);
    make3d(fn, &prm.m[M_WQ], d_in[3], 4096, D_MODEL, 1, 8192, 8192 * D_MODEL, 32, 192, 1, CU_TENSOR_MAP_SWIZZLE_64B, P128);
    for (int x = 0; x < 2; x++) {
        const CUtensorMapSwizzle sp = x ? CU_TENSOR_MAP_SWIZZLE_32B : CU_TENSOR_MAP_SWIZZLE_128B;
        const CUtensorMapSwizzle sg = x ? CU_TENSOR_MAP_SWIZZLE_32B : CU_TENSOR_MAP_SWIZZLE_64B;
        make3d(fn, &prm.m[M_WO + 4 * x], d_in[4], D_MODEL, 4096, 1, D_MODEL * 2, D_MODEL * 2 * 4096, x ? 16 : 64, x ? 128 : 64, 1, sp, P128);
        make3d(fn, &prm.m[M_WD + 4 * x], d_in[8], D_MODEL, FF, 1, D_MODEL * 2, D_MODEL * 2 * FF, x ? 16 : 64, x ? 144 : 48, 1, sp, P128);
        make3d(fn, &prm.m[M_WG + 4 * x], d_in[6], FF, D_MODEL, 1, FF * 2, FF * 2 * D_MODEL, x ? 16 : 32, x ? 192 : 96, 1, sg, P128);
        make3d(fn, &prm.m[M_WU + 4 * x], d_in[7], FF, D_MODEL, 1, FF * 2, FF * 2 * D_MODEL, x ? 16 : 32, x ? 192 : 96, 1, sg, P128);
    }
    void* scr = nullptr;
    void* plan = nullptr;
    cudaGetSymbolAddress(&scr, g_scr);
    cudaGetSymbolAddress(&plan, g_plan);
    fused_block_kernel<<<NCTA, NTHREADS, SM_LAUNCH>>>(prm, (const __nv_bfloat16*)d_in[0], (const __nv_bfloat16*)d_in[9],
                                                     (__nv_bfloat16*)d_out, (uint4*)scr, plan);
}
```

```cpp
#include <cuda_runtime.h>
#include <cuda_bf16.h>
#include <cuda.h>
#include <stdint.h>
#include <stdlib.h>

namespace {

constexpr int D_MODEL = 576;
constexpr int NB = 4;
constexpr int SK = 4096;
constexpr int FF = 4608;
constexpr int NCTA = 128;
constexpr int NTHREADS = 320;
constexpr int NSLOT = 12;
constexpr int TILE_BYTES = 16384;
constexpr int TILES = 32;
constexpr int AV_PITCH = 1168;

constexpr int SM_W0 = 7 * TILE_BYTES;
constexpr int SM_X = 4 * TILE_BYTES;
constexpr int SM_WO = SM_X + 36864;
constexpr int SM_WG = SM_WO + 32768;
constexpr int SM_WD = 12288;
constexpr int SM_GRED = 3 * TILE_BYTES;
constexpr int SM_SC = NSLOT * TILE_BYTES;
constexpr int SM_RED = SM_SC + 8192;
constexpr int SM_AVA = SM_RED + 4096;
constexpr int SM_AVB = SM_AVA + 4 * AV_PITCH;
constexpr int SM_CB1 = SM_AVB + 4 * AV_PITCH;
constexpr int SM_SB = SM_CB1 + 4 * AV_PITCH;
constexpr int SM_QS = SM_SB + 4 * AV_PITCH;
constexpr int SM_XR = SM_QS + 512;
constexpr int SM_BAR = SM_XR + 144;
constexpr int CH_KV = 6, CH_WO = 70, CH_GA = 76, CH_GB = 88, CH_WD = 94, NCHUNK = 100;
constexpr int REL = NCHUNK, RELW = REL + 64, NBAR = RELW + 2;
constexpr int SM_TAB = SM_BAR + 1344;
static_assert(NBAR * 8 <= 1344, "bars");
constexpr int SM_ADJ = SM_TAB + NCHUNK * 16;
constexpr int SM_ORG = SM_ADJ + 16;
constexpr int SM_TOTAL = SM_ORG + 96;
static_assert(SM_TOTAL <= 232448, "smem");
#define NB_ 1
constexpr int NBURST = NB_;
__host__ __device__ constexpr int slot_of(int i) { return i < 48 ? i % NSLOT : ((i - 48) % 6 < 4 ? (i - 48) % 6 : (i - 48) % 6 + 6); }

#define EVF 2
#define NHARD 4
#define HARD_WAIT 0x546
#define KFIRST 36
#define WQ_FREE 0
#define KVPROMO CU_TENSOR_MAP_L2_PROMOTION_L2_256B
#define SLP 40
#define PACE_SLEEP 0
#define SLP_X 0
#define SLP_A 0
#define PFMAP 1
#define NRED 1
#define RED_GAP 90
#define MODAT (1 + cta % 5)
#define SLP_GATE 300
#define GATE_MASK 0
#define SLP_R 0
#define SLP_O 0

constexpr unsigned SPIN_LIMIT = 1u << 22;
constexpr float LOG2E = 1.4426950408889634f;

enum { M_K = 0, M_V, M_WMOD, M_WQ, M_WO, M_WD, M_WG, M_WU, M_WOX, M_WDX, M_WGX, M_WUX, NMAPS };
struct alignas(16) Plan { uint32_t e[128][4]; };
struct Params { CUtensorMap m[NMAPS]; };

constexpr int knob(const char*, int dflt) { return dflt; }
#define PLAN_CONST constexpr

PLAN_CONST Plan make_plan() {
    Plan pl = {};
    const int early_from = knob("EARLY_FROM", 56), early_n = knob("EARLY_N", 0), main_from = knob("MAIN_FROM", 18);
    const int win_start = knob("WIN_START", 48), win_main = knob("WIN_MAIN", 64), win_last = knob("WIN_LAST", 64), n_last = knob("N_LAST", 0);
    const int win_wo = knob("WIN_WO", 48), win_gu = knob("WIN_GU", 44), win_wd = knob("WIN_WD", 32);
    const int lo_main = knob("LO_MAIN", 32), hi_main = knob("HI_MAIN", 32), lag_main = knob("LAG_MAIN", 56);
    const int lo_tail = knob("LO_TAIL", 6), hi_tail = knob("HI_TAIL", 6), lag_tail = knob("LAG_TAIL", 16);
    int cum = 0;
    const unsigned char tail[30] = {70, 74, 71, 75, 72, 73, 76, 77, 84, 85, 78, 79, 80, 81, 86, 87, 82, 83,
                                           88, 89, 92, 93, 90, 91, 94, 95, 96, 97, 98, 99};
    int order[NCHUNK] = {}, n = 0, w = 0, last_tile = 0;
    for (int i = 0; i < 3; i++) order[n++] = i;
    for (int i = 0; i < NBURST; i++) order[n++] = CH_KV + i;
    for (int i = 3; i < 6; i++) order[n++] = i;
    for (int i = NBURST; i < 2 * TILES; i++) {
        last_tile = n;
        order[n++] = CH_KV + i;
        if (i >= early_from && i < 2 * TILES - 1 && w < early_n) order[n++] = tail[w++];
    }
    while (w < 30) order[n++] = tail[w++];
    int last_user[NSLOT] = {};
    for (int i = 0; i < NSLOT; i++) last_user[i] = i >= 9 ? RELW + 1 : i >= 7 ? RELW : 0;
    int bytes_at[NCHUNK] = {};
    for (int p = 0; p < NCHUNK; p++) {
        const int c = order[p];
        const int x = c == 74 || c == 75 ? c - 74 : c >= 84 && c < 88 ? c - 82 : c == 92 || c == 93 ? c - 86 : -1;
        int map = 0, dst = 0, row = 0, bytes = 0;
        if (c < CH_KV) { map = c < 3 ? M_WMOD : M_WQ; dst = SM_W0 + c * 12288; bytes = 12288; row = (c % 3) * 192; }
        else if (c < CH_WO) { const int i = c - CH_KV; map = i / TILES; dst = slot_of(i) * TILE_BYTES; bytes = TILE_BYTES; row = (i % TILES) * 128; }
        else if (x >= 0) { map = 0; dst = SM_X; bytes = 0; row = x; }
        else if (c < CH_GA) { const int t = c - CH_WO; map = M_WO; dst = SM_WO + t * 8192; bytes = 8192; row = t * 64; }
        else if (c < CH_WD) { const int t = c < CH_GB ? c - CH_GA : c - CH_GB + 8; map = M_WG; dst = t < 10 ? SM_WG + t * 6144 : (t - 10) * 6144; bytes = 6144; row = t * 48; }
        else { const int t = c - CH_WD; map = M_WD; dst = SM_WD + t * 6144; bytes = 6144; row = t * 48; }
        bytes_at[p] = bytes ? bytes : 2048;
        unsigned rel = 0, wait = 0;
        if (x >= 0) rel = 0;
        else if (c == CH_WO - 1 - 8) rel = last_user[dst / TILE_BYTES] | (last_user[4] << 8);
        else if (c == CH_WO - 1 - 9) rel = last_user[dst / TILE_BYTES] | (last_user[5] << 8);
        else if (c >= CH_KV) rel = last_user[dst / TILE_BYTES] | (last_user[(dst + bytes - 1) / TILE_BYTES] << 8);
        if (c >= CH_KV && c < CH_WO) last_user[dst / TILE_BYTES] = REL + c - CH_KV;
        const int win = p < main_from ? win_start : p <= last_tile - n_last ? win_main : p <= last_tile ? win_last
                      : c < CH_GA ? win_wo : c < CH_WD ? win_gu : win_wd;
        const bool tl = p > last_tile;
        cum += bytes_at[p] / 1024;
        for (int k = 0; k < 2; k++) {
            const int lim = (p < main_from ? win : k ? win - (tl ? lo_tail : lo_main) : win + (tl ? hi_tail : hi_main)) * 1024;
            int q = p - 1, sum = bytes_at[p];
            while (q > 0 && (sum + bytes_at[q] <= lim || bytes_at[q] == 2048)) sum += bytes_at[q--];
            wait |= (unsigned)order[q < 0 ? 0 : q] << (8 * k);
        }
        const int thr = cum - win - (tl ? lag_tail : lag_main);
        wait = rel | (wait << 16);
        rel = (unsigned)(thr < 0 ? 0 : thr) | ((unsigned)cum << 18);
        pl.e[p][0] = dst | (map << 20) | (c << 24); pl.e[p][1] = row | (bytes << 16); pl.e[p][2] = rel; pl.e[p][3] = wait;
    }
    return pl;
}
__device__ const Plan g_plan = make_plan();

#define NREP_ 4
constexpr int NREP = NREP_;
constexpr int G_CNT = 0;
constexpr int G_H = G_CNT + 8;
constexpr int G_MOD = G_H + NREP * 288;
constexpr int G_Q = G_MOD + 1152;
constexpr int G_STAT = G_Q + 2048;
constexpr int G_OPART = G_STAT + NCTA * 2;
constexpr int G_X1 = G_OPART + NCTA * 64;
constexpr int G_ACT = G_X1 + NREP * 288;
constexpr int G_PART = G_ACT + 2 * 2304;
constexpr int G_TOTAL = G_PART + 2 * 72 * 128;
__device__ __align__(128) uint4 g_scr[G_TOTAL];
#define STAMP(i)
#define STAMPT(t, i)
#define STAMP0(i)
constexpr int SM_LAUNCH = SM_TOTAL;

__device__ __forceinline__ uint32_t enc(uint32_t w) { return max(~w, 1u); }
__device__ __forceinline__ uint32_t encf(float f) { return enc(__float_as_uint(f)); }
__device__ __forceinline__ float decf(uint32_t w) { return __uint_as_float(~w); }
__device__ __forceinline__ float bf_lo(uint32_t w) { return __uint_as_float(w << 16); }
__device__ __forceinline__ float bf_hi(uint32_t w) { return __uint_as_float(w & 0xFFFF0000u); }
__device__ __forceinline__ uint32_t pack_bf(float lo, float hi) {
    uint32_t r;
    asm("cvt.rn.bf16x2.f32 %0, %1, %2;" : "=r"(r) : "f"(hi), "f"(lo));
    return r;
}
__device__ __forceinline__ float bfr(float x) { return __uint_as_float(pack_bf(0.f, x)); }
__device__ __forceinline__ uint32_t mul2(uint32_t a, uint32_t b) { uint32_t r; asm("mul.rn.bf16x2 %0, %1, %2;" : "=r"(r) : "r"(a), "r"(b)); return r; }
__device__ __forceinline__ uint32_t add2(uint32_t a, uint32_t b) { uint32_t r; asm("add.rn.bf16x2 %0, %1, %2;" : "=r"(r) : "r"(a), "r"(b)); return r; }
__device__ __forceinline__ uint32_t sub2(uint32_t a, uint32_t b) { uint32_t r; asm("sub.rn.bf16x2 %0, %1, %2;" : "=r"(r) : "r"(a), "r"(b)); return r; }
__device__ __forceinline__ float ex2(float x) { float r; asm("ex2.approx.ftz.f32 %0, %1;" : "=f"(r) : "f"(x)); return r; }
__device__ __forceinline__ float rcp(float x) { float r; asm("rcp.approx.ftz.f32 %0, %1;" : "=f"(r) : "f"(x)); return r; }
__device__ __forceinline__ float fsqrt(float x) { float r; asm("sqrt.approx.ftz.f32 %0, %1;" : "=f"(r) : "f"(x)); return r; }
__device__ __forceinline__ float sigm(float x) { return rcp(1.0f + ex2(-LOG2E * x)); }
__device__ __forceinline__ float gelu(float g) { return g * sigm(1.5957691216057308f * (g + 0.044715f * g * g * g)); }
__device__ __forceinline__ void mbar_init(uint32_t bar, uint32_t cnt) {
    asm volatile("mbarrier.init.shared::cta.b64 [%0], %1;" ::"r"(bar), "r"(cnt) : "memory");
}
__device__ __forceinline__ void mbar_expect(uint32_t bar, uint32_t bytes) {
    asm volatile("mbarrier.arrive.expect_tx.shared::cta.b64 _, [%0], %1;" ::"r"(bar), "r"(bytes) : "memory");
}
__device__ __forceinline__ void mbar_arrive(uint32_t bar) {
    asm volatile("mbarrier.arrive.shared::cta.b64 _, [%0];" ::"r"(bar) : "memory");
}
__device__ __forceinline__ void mbar_wait(uint32_t bar) {
    asm volatile("{\n.reg .pred p;\n.reg .u32 n;\nmov.u32 n, 0;\n"
                 "W_%=:\nmbarrier.try_wait.parity.shared::cta.b64 p, [%0], 0;\n@p bra D_%=;\n"
                 "add.u32 n, n, 1;\nsetp.lt.u32 p, n, %1;\n@p bra W_%=;\ntrap;\nD_%=:\n}"
                 ::"r"(bar), "n"(SPIN_LIMIT) : "memory");
}
__device__ __forceinline__ bool mbar_test(uint32_t bar) {
    uint32_t ok;
    asm volatile("{\n.reg .pred p;\nmbarrier.test_wait.parity.shared::cta.b64 p, [%1], 0;\nselp.u32 %0, 1, 0, p;\n}" : "=r"(ok) : "r"(bar) : "memory");
    return ok != 0;
}
__device__ __forceinline__ void tma3(uint32_t dst, const CUtensorMap* m, int c0, int c1, int c2, uint32_t bar, uint64_t pol) {
    asm volatile("cp.async.bulk.tensor.3d.shared::cluster.global.mbarrier::complete_tx::bytes.L2::cache_hint [%0], [%1, {%3, %4, %5}], [%2], %6;"
                 ::"r"(dst), "l"(m), "r"(bar), "r"(c0), "r"(c1), "r"(c2), "l"(pol) : "memory");
}
__device__ __forceinline__ void cbar() { asm volatile("bar.sync 1, 256;" ::: "memory"); }
__device__ __forceinline__ void ldsm4(uint32_t (&r)[4], uint32_t a) {
    asm volatile("ldmatrix.sync.aligned.m8n8.x4.shared.b16 {%0,%1,%2,%3}, [%4];"
                 : "=r"(r[0]), "=r"(r[1]), "=r"(r[2]), "=r"(r[3]) : "r"(a) : "memory");
}
__device__ __forceinline__ void ldsm4t(uint32_t (&r)[4], uint32_t a) {
    asm volatile("ldmatrix.sync.aligned.m8n8.x4.trans.shared.b16 {%0,%1,%2,%3}, [%4];"
                 : "=r"(r[0]), "=r"(r[1]), "=r"(r[2]), "=r"(r[3]) : "r"(a) : "memory");
}
__device__ __forceinline__ void mma16816(float (&c)[4], const uint32_t (&a)[4], uint32_t b0, uint32_t b1) {
    asm volatile("mma.sync.aligned.m16n8k16.row.col.f32.bf16.bf16.f32 {%0,%1,%2,%3}, {%4,%5,%6,%7}, {%8,%9}, {%0,%1,%2,%3};"
                 : "+f"(c[0]), "+f"(c[1]), "+f"(c[2]), "+f"(c[3])
                 : "r"(a[0]), "r"(a[1]), "r"(a[2]), "r"(a[3]), "r"(b0), "r"(b1));
}
__device__ __forceinline__ uint32_t lds32(uint32_t a) {
    uint32_t r; asm volatile("ld.shared.b32 %0, [%1];" : "=r"(r) : "r"(a) : "memory"); return r;
}
__device__ __forceinline__ uint32_t lds16(uint32_t a) {
    unsigned short r; asm volatile("ld.shared.b16 %0, [%1];" : "=h"(r) : "r"(a) : "memory"); return r;
}
__device__ __forceinline__ float ldsf(uint32_t a) { return __uint_as_float(lds32(a)); }
__device__ __forceinline__ uint4 lds128(uint32_t a) {
    uint4 r; asm volatile("ld.shared.v4.b32 {%0,%1,%2,%3}, [%4];" : "=r"(r.x), "=r"(r.y), "=r"(r.z), "=r"(r.w) : "r"(a) : "memory"); return r;
}
__device__ __forceinline__ float4 lds128f(uint32_t a) {
    float4 r; asm volatile("ld.shared.v4.f32 {%0,%1,%2,%3}, [%4];" : "=f"(r.x), "=f"(r.y), "=f"(r.z), "=f"(r.w) : "r"(a) : "memory"); return r;
}
__device__ __forceinline__ void sts16(uint32_t a, uint32_t v) { asm volatile("st.shared.b16 [%0], %1;" ::"r"(a), "h"((unsigned short)v) : "memory"); }
__device__ __forceinline__ void sts32(uint32_t a, uint32_t v) { asm volatile("st.shared.b32 [%0], %1;" ::"r"(a), "r"(v) : "memory"); }
__device__ __forceinline__ void sts64(uint32_t a, uint32_t x, uint32_t y) { asm volatile("st.shared.v2.b32 [%0], {%1,%2};" ::"r"(a), "r"(x), "r"(y) : "memory"); }
__device__ __forceinline__ void stsf(uint32_t a, float v) { sts32(a, __float_as_uint(v)); }
__device__ __forceinline__ void sts128(uint32_t a, uint4 v) {
    asm volatile("st.shared.v4.b32 [%0], {%1,%2,%3,%4};" ::"r"(a), "r"(v.x), "r"(v.y), "r"(v.z), "r"(v.w) : "memory");
}
__device__ __forceinline__ void sts128f(uint32_t a, float x, float y, float z, float w) {
    asm volatile("st.shared.v4.f32 [%0], {%1,%2,%3,%4};" ::"r"(a), "f"(x), "f"(y), "f"(z), "f"(w) : "memory");
}
__device__ __forceinline__ float4 sum8(uint32_t a, int st) {
    float4 v[8];
#pragma unroll
    for (int w = 0; w < 8; w++) v[w] = lds128f(a + w * st);
#pragma unroll
    for (int o = 4; o; o >>= 1)
#pragma unroll
        for (int w = 0; w < o; w++) { v[w].x += v[w + o].x; v[w].y += v[w + o].y; v[w].z += v[w + o].z; v[w].w += v[w + o].w; }
    return v[0];
}
__device__ __forceinline__ void pub32(bool p, void* a, uint32_t v) {
    asm volatile("{\n.reg .pred q;\nsetp.ne.u32 q, %2, 0;\n@q st.relaxed.gpu.global.b32 [%0], %1;\n}" ::"l"(a), "r"(v), "r"((uint32_t)p) : "memory");
}
__device__ __forceinline__ void pub64(bool p, void* a, uint32_t x, uint32_t y) {
    asm volatile("{\n.reg .pred q;\nsetp.ne.u32 q, %3, 0;\n@q st.relaxed.gpu.global.v2.b32 [%0], {%1,%2};\n}" ::"l"(a), "r"(x), "r"(y), "r"((uint32_t)p) : "memory");
}
__device__ __forceinline__ void st16(bool p, void* a, uint32_t v) {
    asm volatile("{\n.reg .pred q;\nsetp.ne.u32 q, %2, 0;\n@q st.global.b16 [%0], %1;\n}" ::"l"(a), "h"((unsigned short)v), "r"((uint32_t)p) : "memory");
}
__device__ __forceinline__ void clr128(bool p, void* a) {
    asm volatile("{\n.reg .pred q;\nsetp.ne.u32 q, %1, 0;\n@q st.relaxed.gpu.global.v4.b32 [%0], {%2,%2,%2,%2};\n}" ::"l"(a), "r"((uint32_t)p), "r"(0) : "memory");
}
__device__ __forceinline__ uint32_t back32(bool p, const void* a) {
    uint32_t r = 0;
    asm volatile("{\n.reg .pred q;\nsetp.ne.u32 q, %2, 0;\n@q ld.relaxed.gpu.global.b32 %0, [%1];\n}" : "+r"(r) : "l"(a), "r"((uint32_t)p) : "memory");
    return r;
}
__device__ __forceinline__ void ldg_missing(uint4& r, const uint4* p, uint32_t lo) {
    asm volatile("{\n.reg .pred q;\nsetp.eq.u32 q, %5, 0;\n@q ld.relaxed.gpu.global.v4.b32 {%0,%1,%2,%3}, [%4];\n}"
                 : "+r"(r.x), "+r"(r.y), "+r"(r.z), "+r"(r.w) : "l"(p), "r"(lo) : "memory");
}
__device__ __forceinline__ uint32_t min4(const uint4& v) { return min(min(v.x, v.y), min(v.z, v.w)); }
template <int N, int SLEEP, bool GATE, class Side>
__device__ __forceinline__ void poll(uint4 (&v)[N], const uint4* p, int stride, uint32_t skip, Side side) {
    uint32_t lo[N];
#pragma unroll
    for (int i = 0; i < N; i++) { lo[i] = (skip >> i) & 1; v[i] = make_uint4(lo[i], lo[i], lo[i], lo[i]); }
    uint32_t hold0 = GATE ? threadIdx.x & GATE_MASK : 0, hold = GATE;
#pragma unroll 1
    for (unsigned it = 0;; it++) {
#pragma unroll
        for (int i = 0; i < N; i++) ldg_missing(v[i], p + i * stride, lo[i] | (i ? hold : hold0));
        side();
        uint32_t all = 0xFFFFFFFFu;
#pragma unroll
        for (int i = 0; i < N; i++) { lo[i] = min4(v[i]); all = min(all, lo[i]); }
        if (__all_sync(0xffffffffu, all != 0)) break;
        if (it > SPIN_LIMIT) __trap();
        if (GATE && hold) {
            if (__any_sync(0xffffffffu, lo[0] != 0)) hold0 = hold = 0; else __nanosleep(SLP_GATE);
        } else if (SLEEP) __nanosleep(SLEEP);
    }
}
template <int N, int SLEEP>
__device__ __forceinline__ void poll(uint4 (&v)[N], const uint4* p, int stride) { poll<N, SLEEP, false>(v, p, stride, 0, [] {}); }
__device__ __forceinline__ uint4 unzip(const uint4& e) {
    uint4 r;
    r.x = ~__byte_perm(e.x, e.z, 0x5410);
    r.y = ~__byte_perm(e.x, e.z, 0x7632);
    r.z = ~__byte_perm(e.y, e.w, 0x5410);
    r.w = ~__byte_perm(e.y, e.w, 0x7632);
    return r;
}
__device__ __forceinline__ void put_piece(const uint4& e, uint32_t a) {
    const uint4 u = unzip(e);
    sts32(a, u.x); sts32(a + AV_PITCH, u.y); sts32(a + 2 * AV_PITCH, u.z); sts32(a + 3 * AV_PITCH, u.w);
}
template <class Side>
__device__ __forceinline__ void gather576(const uint4* src, uint32_t dst, int warp, int lane, Side side) {
    uint4 v[2];
    const int t = warp * 36 + lane;
    poll<2, SLP_X, true>(v, src + t, 32, lane < 4 ? 0 : 2, side);
    put_piece(v[0], dst + t * 4);
    if (lane < 4) put_piece(v[1], dst + t * 4 + 128);
}
__device__ __forceinline__ float ln_rden(float var) { return rcp(bfr(fsqrt(bfr(bfr(fmaxf(var, 0.f)) + 1e-5f)))); }
__device__ __forceinline__ void ln_stats(const uint32_t (&w)[9], float& mean_b, float& rden) {
    const float piv = __shfl_sync(0xffffffffu, bf_lo(w[0]), 0);
    float s = 0.f, q = 0.f;
#pragma unroll
    for (int i = 0; i < 9; i++) {
        const float a = bf_lo(w[i]) - piv, c = bf_hi(w[i]) - piv;
        s += a + c;
        q = fmaf(a, a, fmaf(c, c, q));
    }
#pragma unroll
    for (int o = 16; o; o >>= 1) { s += __shfl_xor_sync(0xffffffffu, s, o); q += __shfl_xor_sync(0xffffffffu, q, o); }
    s *= (1.0f / D_MODEL);
    mean_b = bfr(piv + s);
    rden = ln_rden(fmaf(q, 1.0f / D_MODEL, -s * s));
}
__device__ __forceinline__ float ln_mod(float x, float mean_b, float rden, float scale1, float shift) {
    return bfr(bfr(bfr(x - mean_b) * rden) * scale1) + shift;
}

__device__ __forceinline__ uint32_t ln_mod2(uint32_t x, uint32_t mean2, float rden, uint32_t scale1, uint32_t shift) {
    const uint32_t d = sub2(x, mean2);
    return add2(mul2(pack_bf(bf_lo(d) * rden, bf_hi(d) * rden), scale1), shift);
}
__device__ __forceinline__ bool landed(uint32_t bars, int first, int n, int lane) {
    return __all_sync(0xffffffffu, mbar_test(bars + (first + min(lane, n - 1)) * 8));
}
__device__ __forceinline__ void wait_landed(uint32_t bars, int first, int n, int lane) {
    if (lane < n) mbar_wait(bars + (first + lane) * 8);
    __syncwarp();
}

__global__ void __launch_bounds__(NTHREADS, 1)
fused_block_kernel(const __grid_constant__ Params prm, const __nv_bfloat16* __restrict__ x, const __nv_bfloat16* __restrict__ cvec,
                   __nv_bfloat16* __restrict__ out, uint4* __restrict__ scr, const void* __restrict__ plan) {
    extern __shared__ __align__(1024) unsigned char smem_raw[];
    const uint32_t sm = (uint32_t)__cvta_generic_to_shared(smem_raw);
    const uint32_t bars = sm + SM_BAR;
    const int tid = threadIdx.x, warp = __shfl_sync(0xffffffffu, tid >> 5, 0), lane = tid & 31;
    const int cta = blockIdx.x;
    const int g = cta >> 3, j = cta & 7, b = j >> 1, s = j & 1;
    const int f0 = (g >> 1) * 576 + j * 64, fx = (g >> 1) * 576 + 448 + j * 16;
    const bool xg = j >= 4;

    const int row0 = (b * 16 + g) * SK + s * 64;
    if (warp >= 8) {
    if (warp == 8) {
        uint64_t pol_kv, pol_w;
        asm volatile("createpolicy.fractional.L2::evict_first.b64 %0, 1.0;" : "=l"(pol_kv));
        asm volatile("createpolicy.fractional.L2::evict_normal.b64 %0, 1.0;" : "=l"(pol_w));
        if (!EVF) pol_kv = pol_w;
        if (EVF == 2) pol_w = pol_kv;
        if (lane == 0) {
#pragma unroll
            for (int n = 0; n < 6 + NBURST; n++) if (n < 3 || n >= 6) mbar_init(bars + n * 8, 1);
            asm volatile("fence.mbarrier_init.release.cluster;" ::: "memory");
            auto burst = [&]() {
#pragma unroll
                for (int n = 0; n < NBURST; n++) {
                    mbar_expect(bars + (CH_KV + n) * 8, TILE_BYTES);
                    tma3(sm + n * TILE_BYTES, &prm.m[M_K], 0, row0 + n * 128, 0, bars + (CH_KV + n) * 8, pol_kv);
                }
            };
            if (cta >= KFIRST) burst();
#pragma unroll
            for (int n = 0; n < 3; n++) {
                mbar_expect(bars + n * 8, cta < 108 ? 12288 : 0);
                if (cta < 108) tma3(sm + SM_W0 + n * 12288, &prm.m[M_WMOD], (cta % 36) * 16, n * 192, (cta / 36) * 2, bars + n * 8, pol_w);
            }
            if (cta < KFIRST) burst();
            STAMP(46);
#pragma unroll
            for (int n = 3; n < 12; n++) if (n < 6 || n >= 6 + NBURST) mbar_init(bars + n * 8, 1);
            mbar_init(bars + RELW * 8, 1);
            mbar_init(bars + (RELW + 1) * 8, 1);
            asm volatile("fence.mbarrier_init.release.cluster;" ::: "memory");
        }
        __syncwarp();
        asm volatile("bar.arrive 4, %0;" ::"n"(NTHREADS) : "memory");
        if (lane == 0) {
#pragma unroll 1
            for (int n = 0; n < 3; n++) {
                mbar_expect(bars + (3 + n) * 8, 12288);
                if (n >= WQ_FREE) mbar_wait(bars + (n - WQ_FREE) * 8);
                tma3(sm + SM_W0 + (3 + n) * 12288, &prm.m[M_WQ], cta * 32, n * 192, 0, bars + (3 + n) * 8, pol_w);
            }
#pragma unroll 1
            for (int n = NBURST; n < NHARD; n++) {
                mbar_expect(bars + (CH_KV + n) * 8, TILE_BYTES);
                mbar_wait(bars + ((HARD_WAIT >> (4 * (n - NBURST))) & 15) * 8);
                tma3(sm + n * TILE_BYTES, &prm.m[M_K], 0, row0 + n * 128, 0, bars + (CH_KV + n) * 8, pol_kv);
            }
        }
        __syncwarp();
        asm volatile("bar.sync 2, 64;" ::: "memory");
        if (sm & 1023) __trap();
        uint4 e = lds128(sm + SM_TAB + (6 + NHARD) * 16);
#pragma unroll 1
        for (int p = 6 + NHARD; p < NCHUNK; p++) {
            const uint4 nx = lds128(sm + SM_TAB + (p + 1) * 16);
            if (e.x & 0x80000u) {
                const uint32_t tb = bars + ((e.w >> ((lane & 3) * 8)) & 255) * 8;
#pragma unroll 1
                for (unsigned it = 0;; it++) {
                    const bool far = lds32(sm + SM_ADJ) >= (e.y >> 16);
                    if (__all_sync(0xffffffffu, mbar_test(tb) || ((lane & 3) == 3 && far))) break;
                    if (it > 16 * SPIN_LIMIT) __trap();
                }
                if (lane == 0) {
                    tma3(sm + (e.x & 0x7FFFF), &prm.m[(e.x >> 20) & 15], e.y & 0xFFFF, e.z & 0x3FFFF, 0, bars + (e.x >> 24) * 8,
                         (e.x & 0xE00000u) ? pol_w : pol_kv);
                }
            }
            e = nx;
        }
    } else if (warp == 9) {
        if (lane < NMAPS)
            sts64(sm + SM_ORG + lane * 8,
                  lane <= M_V ? 0 : lane <= M_WQ ? cta * 32 : lane <= M_WD ? j * 64 : lane <= M_WU ? f0 : lane <= M_WDX ? 512 + j * 16 : fx,
                  lane <= M_V ? row0 : (lane & 2) ? 0 : (lane & 1) ? g * 288 : g * 256);
        if (lane == 0) sts32(sm + SM_ADJ, 0);
        uint4 pe[4];
#pragma unroll
        for (int i = 0; i < 4; i++) pe[i] = __ldg(reinterpret_cast<const uint4*>(plan) + min(lane + 32 * i, NCHUNK - 1));
        asm volatile("bar.sync 4, %0;" ::"n"(NTHREADS) : "memory");
#pragma unroll
        for (int i = 0; i < 4; i++) {
            if ((pe[i].y >> 16) == 0) {
                const uint32_t t = pe[i].y, h = t & 1;
                pe[i].x += xg ? ((t >> 1) - 1) * 6144 + (M_WGX << 20) : t < 2 ? h * 4096 + (M_WOX << 20) : 8192 + h * 4608 + (M_WDX << 20);
                pe[i].y = xg ? (t < 2 || h ? 0 : ((t >> 1) - 1) * 192 + (6144 << 16))
                             : t < 2 ? h * 128 + (4096 << 16) : t >= 6 ? h * 144 + (4608 << 16) : 0;
            }
            if (((pe[i].x >> 20) & 3) == 2 && (pe[i].x >> 24) >= CH_WO) pe[i].x += (g & 1) << 20;
            const int p = lane + 32 * i;
            if (p < NCHUNK) {
                const uint32_t org = sm + SM_ORG + ((pe[i].x >> 20) & 15) * 8;
                if (p >= 6 + NHARD) mbar_expect(bars + (pe[i].x >> 24) * 8, pe[i].y >> 16);
                sts128(sm + SM_TAB + p * 16, make_uint4(pe[i].x | ((pe[i].y >> 16) ? 0x80000u : 0u), lds32(org) | (pe[i].z << 16),
                                                        (lds32(org + 4) + (pe[i].y & 0xFFFF)) | (pe[i].z & 0xFFFC0000u), pe[i].w));
            }
        }
        asm volatile("bar.arrive 2, 64;" ::: "memory");
        __syncwarp();
        if (PFMAP && lane < NMAPS) asm volatile("prefetch.tensormap [%0];" ::"l"(&prm.m[lane]) : "memory");
        if (lane == 0) {
            int n = 0;
            uint32_t kb = 0;
#pragma unroll 1
            for (unsigned it = 0; n < NCHUNK; it++) {
                while (n < NCHUNK && mbar_test(bars + (lds32(sm + SM_TAB + n * 16) >> 24) * 8)) n++;
                const uint32_t now = n == NCHUNK ? 2048 : n ? lds32(sm + SM_TAB + n * 16 - 8) >> 18 : 0;
                sts32(sm + SM_ADJ, (atomicAdd(reinterpret_cast<unsigned*>(scr + G_CNT), now - kb) & 0x3FFFFu) >> 7);
                kb = now;
                if (it > SPIN_LIMIT) __trap();
                if (PACE_SLEEP) __nanosleep(PACE_SLEEP);
            }
        }
    }
    } else {
    uint2 cw[3];
    uint32_t xw[9];
#pragma unroll
    for (int i = 0; i < 3; i++) cw[i] = cta < 108 ? __ldg(reinterpret_cast<const uint2*>(cvec) + min(tid + 256 * i, 575)) : make_uint2(0, 0);
#pragma unroll
    for (int i = 0; i < 9; i++) xw[i] = cta < 36 && warp >= 4 ? __ldg(reinterpret_cast<const uint32_t*>(x) + (warp & 3) * 288 + lane + 32 * i) : 0u;
    static_assert(G_OPART - G_Q == 36 * 64, "clear split");
    clr128(cta < 36 && tid < 64, scr + (G_Q + cta * 64 + tid));
    uint32_t cleared = back32(cta < 36 && tid < 64, scr + (G_Q + cta * 64 + tid));
    if (lane == 0) {
        static_assert(NCHUNK == 12 + 88, "11 chunk barriers and 8 release barriers per warp");
#pragma unroll
        for (int n = 0; n < 11; n++) mbar_init(bars + (12 + warp * 11 + n) * 8, 1);
#pragma unroll
        for (int n = 0; n < 8; n++) mbar_init(bars + (REL + warp * 8 + n) * 8, 2);
        asm volatile("fence.mbarrier_init.release.cluster;" ::: "memory");
    }
    asm volatile("bar.sync 4, %0;" ::"n"(NTHREADS) : "memory");
    const int mi = lane >> 3, r8 = lane & 7;
    const uint32_t bfrag = ((lane >> 2) & 3) * AV_PITCH + (lane & 3) * 4;
    uint32_t* const scr32 = reinterpret_cast<uint32_t*>(scr);
    uint2* const scr64 = reinterpret_cast<uint2*>(scr);
    const int pr = warp >> 1, hf = warp & 1;

#pragma unroll
    for (int i = 0; i < 3; i++) {
        const int p = min(tid + 256 * i, 575);
        const float a0 = bf_lo(cw[i].x), a1 = bf_hi(cw[i].x), a2 = bf_lo(cw[i].y), a3 = bf_hi(cw[i].y);
        sts64(sm + SM_AVA + (p / 144) * AV_PITCH + (p % 144) * 8, pack_bf(a0 * sigm(a0), a1 * sigm(a1)), pack_bf(a2 * sigm(a2), a3 * sigm(a3)));
    }
    if (cta < 36 && warp >= 4) {
        float mean_b, rden;
        ln_stats(xw, mean_b, rden);
        if (lane == 0) sts64(sm + SM_QS + (warp & 3) * 8, __float_as_uint(mean_b), __float_as_uint(rden));
#pragma unroll
        for (int i = 0; i < 9; i++) sts32(sm + SM_CB1 + (warp & 3) * 1152 + (lane + 32 * i) * 4, xw[i]);
    }
    if (cleared) __trap();
    uint32_t mod_lo = 0, mod_hi = 0;
#pragma unroll 1
    for (int it = 0; it < 2; it++) {
        if (it == 1) gather576(scr + (G_H + (g % NREP) * 288), sm + SM_AVB, warp, lane, [] {});
        cbar();
        if (cta < 108 || it == 1) {
            STAMP0(1 + 2 * it);
            const int k = (mi >> 1) * 8 + r8;
            const uint32_t base = sm + SM_W0 + (it ? 36864 + k * 64 : (mi & 1) * 6144 + k * 32);
            const uint32_t ch = it ? (((mi & 1) * 2) ^ (r8 >> 1)) : (r8 >> 2);
            const uint32_t a0 = base + (ch << 4), a1 = base + ((ch ^ 1) << 4), kb = it ? 1024 : 512;
            const uint32_t bb = sm + (it ? SM_AVB : SM_AVA) + bfrag + warp * 32;
            float c0[4] = {0.f, 0.f, 0.f, 0.f}, c1[4] = {0.f, 0.f, 0.f, 0.f};
            uint32_t bq[5][2];
#pragma unroll
            for (int i = 0; i < 5; i++) { bq[i][0] = lds32(bb + i * 256); bq[i][1] = lds32(bb + i * 256 + 16); }
            if (warp >= 4) bq[4][0] = bq[4][1] = 0;
#pragma unroll
            for (int i = 0; i < 3; i++) mbar_wait(bars + (it * 3 + i) * 8);
#pragma unroll
            for (int i = 0; i < 5; i++) {
                const int ks = min(warp + 8 * i, 35);
                const int cq = ks / 12;
                const uint32_t off = cq * 12288 + (ks - cq * 12) * kb;
                uint32_t u[4], v[4];
                ldsm4t(u, a0 + off);
                ldsm4t(v, a1 + off);
                mma16816(c0, u, bq[i][0], bq[i][1]);
                mma16816(c1, v, bq[i][0], bq[i][1]);
            }
            const bool t1 = (lane & 2) != 0;
            sts128f(sm + SM_RED + warp * 512 + (t1 ? 256 : 0) + ((lane >> 2) * 2 + (lane & 1)) * 16,
                    t1 ? c1[0] : c0[0], t1 ? c1[1] : c0[1], t1 ? c1[2] : c0[2], t1 ? c1[3] : c0[3]);
            cbar();
            if (warp == 7) {
                const float4 r = sum8(sm + SM_RED + lane * 16, 512);
                if (it == 0 && cta < 36) {
                    const uint32_t xp = sm + SM_CB1 + (lane & 1) * 2304 + (cta * 16 + (lane >> 1)) * 2;
                    const float4 st = lds128f(sm + SM_QS + (lane & 1) * 16);
                    const float h0 = ln_mod(bf_lo(lds16(xp)), st.x, st.y, bfr(1.0f + bfr(r.z)), bfr(r.x));
                    const float h1 = ln_mod(bf_lo(lds16(xp + 1152)), st.z, st.w, bfr(1.0f + bfr(r.w)), bfr(r.y));
                    const uint32_t hv = enc(pack_bf(h0, h1));
#pragma unroll
                    for (int i = 0; i < NREP; i++) pub32(true, scr32 + (G_H * 4 + i * 1152 + cta * 32 + lane), hv);
                } else {
                    const uint32_t lo = enc(pack_bf(r.x, r.y)), hi = enc(pack_bf(r.z, r.w));
                    pub32(it, scr32 + (G_Q * 4 + cta * 64 + lane), lo);
                    pub32(it, scr32 + (G_Q * 4 + cta * 64 + 32 + lane), hi);
                    if (it == 0) { mod_lo = lo; mod_hi = hi; }
                }
            }
        }
        if (tid == 192) mbar_arrive(bars + (RELW + it) * 8);
    }

    {
        constexpr int PER = (G_TOTAL - G_OPART + 71) / 72;
        static_assert(PER <= 512, "clear split");
        const int i = G_OPART + (cta - 36) * PER + tid;
        const bool p0 = cta >= 36 && i < G_TOTAL, p1 = cta >= 36 && tid + 256 < PER && i + 256 < G_TOTAL;
        clr128(p0, scr + i);
        clr128(p1, scr + i + 256);
        cleared = back32(p0, scr + i) | back32(p1, scr + i + 256);
    }
    if (tid < 128) {
        uint4 v[1];
        poll<1, SLP>(v, scr + (G_Q + g * 128 + tid), 0);
        const uint4 u = unzip(v[0]);
        sts32(sm + SM_QS + tid * 4, b == 0 ? u.x : b == 1 ? u.y : b == 2 ? u.z : u.w);
    }
    if (cleared) __trap();
    cbar();
    if (warp == 7) {
        uint32_t* dst = scr32 + (G_MOD * 4 + ((cta / 72) * 1152 + (cta % 36) * 16) * 2 + lane);
        pub32(cta >= 36 && cta < 108, dst, mod_lo);
        pub32(cta >= 36 && cta < 108, dst + 1152, mod_hi);
    }
    STAMP0(5);
    {
        uint32_t qf[8][2];
#pragma unroll
        for (int ks = 0; ks < 8; ks++) {
            const uint32_t a = sm + SM_QS + ((lane >> 2) & 1) * 256 + ks * 32 + (lane & 3) * 4;
            qf[ks][0] = lds32(a); qf[ks][1] = lds32(a + 16);
        }
        const uint32_t koff = (hf * 32 + (mi & 1) * 8 + r8) * 128;
        uint32_t sw[4];
#pragma unroll
        for (int c = 0; c < 4; c++) sw[c] = koff + (((2 * c + (mi >> 1)) ^ r8) << 4);
#pragma unroll 1
        for (int i = pr; i < TILES; i += 4) {
            mbar_wait(bars + (CH_KV + i) * 8);
            const uint32_t tb = sm + (i % NSLOT) * TILE_BYTES;
            float c[4][4];
#pragma unroll
            for (int u = 0; u < 4; u++) { c[u][0] = c[u][1] = c[u][2] = c[u][3] = 0.f; }
#pragma unroll
            for (int ks = 0; ks < 4; ks++) {
#pragma unroll
                for (int u = 0; u < 4; u++) {
                    uint32_t a[4];
                    ldsm4(a, tb + (u >> 1) * 8192 + (u & 1) * 2048 + sw[ks]);
                    mma16816(c[u], a, qf[(u >> 1) * 4 + ks][0], qf[(u >> 1) * 4 + ks][1]);
                }
            }
            __syncwarp();
            if (lane == 0) mbar_arrive(bars + (REL + i) * 8);
            const bool t1 = (lane & 2) != 0, hi = (lane & 1) != 0;
            const float p0 = t1 ? (hi ? c[1][2] + c[3][2] : c[1][0] + c[3][0]) : (hi ? c[0][2] + c[2][2] : c[0][0] + c[2][0]);
            const float p1 = t1 ? (hi ? c[1][3] + c[3][3] : c[1][1] + c[3][1]) : (hi ? c[0][3] + c[2][3] : c[0][1] + c[2][1]);
            const uint32_t w = pack_bf(bfr(p0) * 0.08838834764831845f, bfr(p1) * 0.08838834764831845f);
            const uint32_t a = sm + SM_SC + (i * 64 + hf * 32 + (lane & 3) * 8 + (lane >> 2)) * 2;
            sts16(a, w & 0xFFFFu);
            sts16(a + 4096, w >> 16);
        }
    }
    cbar();
    STAMP0(6);

    {
        const uint32_t a = sm + SM_SC + tid * 32;
        const uint4 u0 = lds128(a), u1 = lds128(a + 16);
        const uint32_t w[8] = {u0.x, u0.y, u0.z, u0.w, u1.x, u1.y, u1.z, u1.w};
        float e[16], m = -INFINITY;
#pragma unroll
        for (int i = 0; i < 8; i++) { e[2 * i] = bf_lo(w[i]); e[2 * i + 1] = bf_hi(w[i]); m = fmaxf(m, fmaxf(e[2 * i], e[2 * i + 1])); }
#pragma unroll
        for (int o = 16; o; o >>= 1) m = fmaxf(m, __shfl_xor_sync(0xffffffffu, m, o));
        float l = 0.f;
#pragma unroll
        for (int i = 0; i < 16; i++) { e[i] = ex2((e[i] - m) * LOG2E); l += e[i]; }
#pragma unroll
        for (int o = 16; o; o >>= 1) l += __shfl_xor_sync(0xffffffffu, l, o);
        if (lane == 0) { stsf(sm + SM_RED + warp * 4, m); stsf(sm + SM_RED + 32 + warp * 4, l); }
        cbar();
        if (warp == 5) {
            const float4 m4 = lds128f(sm + SM_RED + (lane & 1) * 16), l4 = lds128f(sm + SM_RED + 32 + (lane & 1) * 16);
            const float mm = fmaxf(fmaxf(m4.x, m4.y), fmaxf(m4.z, m4.w));
            const float ll = (l4.x * ex2((m4.x - mm) * LOG2E) + l4.y * ex2((m4.y - mm) * LOG2E)) +
                             (l4.z * ex2((m4.z - mm) * LOG2E) + l4.w * ex2((m4.w - mm) * LOG2E));
            pub64(lane < 4, scr64 + (G_STAT * 2 + cta * 4 + lane), encf(mm), encf(ll));
            uint4 v[1];
            poll<1, SLP>(v, scr + (G_STAT + (cta ^ 1) * 2), 0);
            const float mo = decf((lane & 1) ? v[0].z : v[0].x), lo = decf((lane & 1) ? v[0].w : v[0].y);
            const float mg = fmaxf(mm, mo);
            sts64(sm + SM_RED + 64 + (lane & 1) * 8, __float_as_uint(mg),
                  __float_as_uint(rcp(ll * ex2((mm - mg) * LOG2E) + lo * ex2((mo - mg) * LOG2E))));
        }
        cbar();
        const uint32_t st = sm + SM_RED + 64 + (tid >> 7) * 8;
        const float f = ex2((m - ldsf(st)) * LOG2E) * ldsf(st + 4);
        uint4 o0, o1;
        o0.x = pack_bf(e[0] * f, e[1] * f); o0.y = pack_bf(e[2] * f, e[3] * f); o0.z = pack_bf(e[4] * f, e[5] * f); o0.w = pack_bf(e[6] * f, e[7] * f);
        o1.x = pack_bf(e[8] * f, e[9] * f); o1.y = pack_bf(e[10] * f, e[11] * f); o1.z = pack_bf(e[12] * f, e[13] * f); o1.w = pack_bf(e[14] * f, e[15] * f);
        sts128(a, o0); sts128(a + 16, o1);
        cbar();
    }
    STAMP0(7);

    uint32_t wa[2][18][4];
    const bool pw = warp < 4 || (warp == 4 && j < 4);
    const uint32_t astep = warp < 4 ? 2048 : 512;
    const uint32_t aoff = warp < 4 ? ((mi >> 1) * 8 + r8) * 128 + (((warp * 2 + (mi & 1)) ^ r8) << 4)
                                   : ((mi >> 1) * 8 + r8) * 32 + (((mi & 1) ^ (r8 >> 2)) << 4);
    const uint32_t abase[2] = {sm + (warp < 4 ? SM_WO : SM_X) + aoff, sm + (warp < 4 ? SM_WD : SM_X + 8192) + aoff};
    bool have0 = false, have1 = false;
    auto proj_bar = [&](int rd) { return bars + (warp < 4 ? (rd ? CH_WD : CH_WO) + min(lane, 3 + 2 * rd) : (rd ? CH_GB : CH_WO) + 4 + (lane & 1)) * 8; };
    auto proj_load = [&](int rd, uint32_t lb) {
        if (!have0 && (~lb & ((8u << rd) - 1)) == 0) {
            have0 = true;
#pragma unroll
            for (int u = 0; u < 12; u++) ldsm4t(wa[rd][u], abase[rd] + u * astep);
        }
        if (!have1 && lb == 0xFFFFFFFFu) {
            have1 = true;
#pragma unroll
            for (int u = 12; u < 16 + 2 * rd; u++) ldsm4t(wa[rd][u], abase[rd] + u * astep);
        }
    };
    {
        float o[4][4];
#pragma unroll
        for (int u = 0; u < 4; u++) { o[u][0] = o[u][1] = o[u][2] = o[u][3] = 0.f; }
        const uint32_t voff = hf * 8192 + ((mi >> 1) * 8 + r8) * 128;
        uint32_t sw[4];
#pragma unroll
        for (int u = 0; u < 4; u++) sw[u] = voff + (((2 * u + (mi & 1)) ^ r8) << 4);
        const uint32_t pb = sm + SM_SC + ((lane >> 2) & 1) * 4096 + (lane & 3) * 4 - TILES * 128;
        auto fetch_mod = [&]() {
            if (warp < 5) {
            const int t = min(tid, 143);
            uint4 v[4];
            poll<4, SLP>(v, scr + (G_MOD + 288 + t), 144);
#pragma unroll
            for (int i = 0; i < 4; i++) {
                uint4 u = unzip(v[i]);
                if (i >= 2) {
                    u.x = pack_bf(1.0f + bf_lo(u.x), 1.0f + bf_hi(u.x)); u.y = pack_bf(1.0f + bf_lo(u.y), 1.0f + bf_hi(u.y));
                    u.z = pack_bf(1.0f + bf_lo(u.z), 1.0f + bf_hi(u.z)); u.w = pack_bf(1.0f + bf_lo(u.w), 1.0f + bf_hi(u.w));
                }
                const uint32_t d = sm + (i >= 2 ? SM_CB1 : SM_SB) + (t + 144 * (i & 1)) * 4;
                sts32(d, u.x); sts32(d + AV_PITCH, u.y); sts32(d + 2 * AV_PITCH, u.z); sts32(d + 3 * AV_PITCH, u.w);
            }
        } else if (warp == 7 && cta < 72) {
            sts16(sm + SM_XR + (lane & 7) * 8 + (lane >> 3) * 2,
                  reinterpret_cast<const unsigned short*>(x)[(lane >> 3) * D_MODEL + cta * 8 + (lane & 7)]);
            sts64(sm + SM_XR + 128, 0, 0);
            uint4 v[2];
            poll<2, SLP>(v, scr + (G_MOD + cta * 4 + ((lane & 7) >> 1)), 864);
            sts128(sm + SM_QS + (lane & 7) * 16, make_uint4(~((lane & 1) ? v[0].z : v[0].x), ~((lane & 1) ? v[0].w : v[0].y),
                                                            ~((lane & 1) ? v[1].z : v[1].x), ~((lane & 1) ? v[1].w : v[1].y)));
        }
        };
        auto v_tile = [&](int i) {
            uint32_t pf[4][2];
#pragma unroll
            for (int kk = 0; kk < 4; kk++) { pf[kk][0] = lds32(pb + i * 128 + kk * 32); pf[kk][1] = lds32(pb + i * 128 + kk * 32 + 16); }
            const uint32_t tb = sm + slot_of(i) * TILE_BYTES;
            mbar_wait(bars + (CH_KV + i) * 8);
#pragma unroll
            for (int kk = 0; kk < 4; kk++) {
#pragma unroll
                for (int u = 0; u < 4; u++) {
                    uint32_t a[4];
                    ldsm4t(a, tb + kk * 2048 + sw[u]);
                    mma16816(o[u], a, pf[kk][0], pf[kk][1]);
                }
            }
            __syncwarp();
            if (lane == 0) mbar_arrive(bars + (REL + i) * 8);
        };
#pragma unroll 1
        for (int i = TILES + pr; i < 2 * TILES; i += 4) {
            v_tile(i);
            if (((i - TILES) >> 2) == MODAT) fetch_mod();
        }
        const int u = lane & 3;
        float v[4];
#pragma unroll
        for (int q = 0; q < 4; q++) v[q] = u == 0 ? o[0][q] : u == 1 ? o[1][q] : u == 2 ? o[2][q] : o[3][q];
        const uint32_t a = sm + SM_RED + pr * 1024 + (hf * 64 + u * 16 + (lane >> 2)) * 4;
        stsf(a, v[0]); stsf(a + 512, v[1]); stsf(a + 32, v[2]); stsf(a + 512 + 32, v[3]);
    }
    cbar();
    {
        const uint32_t r = sm + SM_RED + tid * 4;
        pub32(true, scr32 + (G_OPART * 4 + cta * 256 + tid), encf((ldsf(r) + ldsf(r + 1024)) + (ldsf(r + 2048) + ldsf(r + 3072))));
        STAMPT(0, 8);
        uint4 v[2];
        poll<2, SLP_O, false>(v, scr + (G_OPART + (g * 8 + (tid >> 6) * 2) * 64 + (tid & 63)), 64, 0,
                              [&] { if (pw && !have1) proj_load(0, __ballot_sync(0xffffffffu, mbar_test(proj_bar(0)))); });
        sts64(sm + SM_AVA + (tid >> 6) * AV_PITCH + (tid & 63) * 8,
              pack_bf(decf(v[0].x) + decf(v[1].x), decf(v[0].y) + decf(v[1].y)),
              pack_bf(decf(v[0].z) + decf(v[1].z), decf(v[0].w) + decf(v[1].w)));
    }

#pragma unroll
    for (int rd = 0; rd < 2; rd++) {
        STAMPT(0, 34 + rd);
        if (rd == 0) cbar(); else if (warp < 5) asm volatile("bar.sync 3, 160;" ::: "memory");
        STAMP0(9 + 5 * rd);
        if (pw) {
            bool t = mbar_test(proj_bar(rd));
            uint32_t b4[9][4];
#pragma unroll
            for (int u = 0; u < 8 + rd; u++) ldsm4(b4[u], sm + SM_AVA + (r8 & 3) * AV_PITCH + mi * 16 + u * 64);
            float c[4][4];
#pragma unroll
            for (int u = 0; u < 4; u++) { c[u][0] = c[u][1] = c[u][2] = c[u][3] = 0.f; }
            if (!have1) {
#pragma unroll 1
                for (unsigned it = 0;; it++) {
                    proj_load(rd, __ballot_sync(0xffffffffu, t));
                    if (have0) break;
                    t = mbar_test(proj_bar(rd));
                    if (it > SPIN_LIMIT) __trap();
                }
            }
#pragma unroll
            for (int u = 0; u < 12; u++) mma16816(c[u & 3], wa[rd][u], b4[u >> 1][(u & 1) * 2], b4[u >> 1][(u & 1) * 2 + 1]);
            if (!have1) {
#pragma unroll 1
                for (unsigned it = 0; !__all_sync(0xffffffffu, mbar_test(proj_bar(rd))); it++)
                    if (it > 16 * SPIN_LIMIT) __trap();
#pragma unroll
                for (int u = 12; u < 16 + 2 * rd; u++) ldsm4t(wa[rd][u], abase[rd] + u * astep);
            }
#pragma unroll
            for (int u = 12; u < 16 + 2 * rd; u++) mma16816(c[u & 3], wa[rd][u], b4[u >> 1][(u & 1) * 2], b4[u >> 1][(u & 1) * 2 + 1]);
            const bool hi = (lane & 2) != 0;
            const int ob = (warp < 4 ? j * 8 + warp * 2 : 64 + j * 2) + (hi ? 1 : 0);
            pub64(true, scr64 + ((G_PART + rd * 72 * 128 + (ob * 16 + g) * 8) * 2 + (lane >> 2) * 2 + (lane & 1)),
                  encf(hi ? (c[2][2] + c[3][2]) + (c[0][2] + c[1][2]) : (c[2][0] + c[3][0]) + (c[0][0] + c[1][0])),
                  encf(hi ? (c[2][3] + c[3][3]) + (c[0][3] + c[1][3]) : (c[2][1] + c[3][1]) + (c[0][1] + c[1][1])));
            STAMPT(0, 10 + 5 * rd);
        } else if (warp >= 8 - NRED && cta < 72) {
            const uint32_t g01 = lds32(sm + SM_QS + (lane & 7) * 16 + rd * 8), g23 = lds32(sm + SM_QS + (lane & 7) * 16 + rd * 8 + 4);
            const uint32_t r01 = lds32(sm + SM_XR + rd * 64 + (lane & 7) * 8), r23 = lds32(sm + SM_XR + rd * 64 + 4 + (lane & 7) * 8);
            uint4 w[4];
            if (warp < 7) __nanosleep((7 - warp) * RED_GAP);
            poll<4, SLP_R>(w, scr + (G_PART + rd * 72 * 128 + cta * 128 + lane), 32);
            if (lds32(sm + SM_XR + 128 + rd * 4) == 0) {
                sts32(sm + SM_XR + 128 + rd * 4, 1);
                float t[4] = {(decf(w[0].x) + decf(w[1].x)) + (decf(w[2].x) + decf(w[3].x)), (decf(w[0].y) + decf(w[1].y)) + (decf(w[2].y) + decf(w[3].y)),
                              (decf(w[0].z) + decf(w[1].z)) + (decf(w[2].z) + decf(w[3].z)), (decf(w[0].w) + decf(w[1].w)) + (decf(w[2].w) + decf(w[3].w))};
#pragma unroll
                for (int q = 0; q < 4; q++) t[q] += __shfl_xor_sync(0xffffffffu, t[q], 8);
#pragma unroll
                for (int q = 0; q < 4; q++) t[q] += __shfl_xor_sync(0xffffffffu, t[q], 16);
                const uint32_t x01 = add2(r01, mul2(g01, pack_bf(t[0], t[1]))), x23 = add2(r23, mul2(g23, pack_bf(t[2], t[3])));
                if (rd == 1) {
                    const uint32_t ov = (lane & 16) ? x23 : x01;
                    st16(true, out + ((lane >> 3) * D_MODEL + cta * 8 + (lane & 7)), (lane & 8) ? ov >> 16 : ov);
                } else {
#pragma unroll
                    for (int i = 0; i < (NREP + 3) / 4; i++)
                        pub64(i * 4 + (lane >> 3) < NREP, scr64 + (G_X1 * 2 + (i * 4 + (lane >> 3)) * 576 + cta * 8 + (lane & 7)), enc(x01), enc(x23));
                    sts64(sm + SM_XR + 64 + (lane & 7) * 8, x01, x23);
                }
            }
        }
        if (rd == 1) break;

        uint32_t wg[5][5][4];
        const bool four = warp >= 4;
        auto load_gu = [&](int i0, int i1) {
#pragma unroll
            for (int i = i0; i < i1; i++) {
                if (i < 4 || !four) {
                    const int ks = warp + 8 * i, k = ks * 16 + (mi >> 1) * 8 + r8;
                    const uint32_t ag = sm + (ks < 30 ? SM_WG : -61440) + k * 128;
#pragma unroll
                    for (int u = 0; u < 4; u++) ldsm4t(wg[i][u], ag + (((2 * u + (mi & 1)) ^ r8) << 4));
                    if (xg) ldsm4t(wg[i][4], sm + SM_X + k * 32 + (((mi & 1) ^ (r8 >> 2)) << 4));
                }
            }
        };
        auto mma_gu = [&](float (&c)[5][4], const uint32_t (&bq)[5][2], int i0, int i1) {
#pragma unroll
            for (int i = i0; i < i1; i++) {
                if (i < 4 || !four) {
#pragma unroll
                    for (int u = 0; u < 4; u++) mma16816(c[u], wg[i][u], bq[i][0], bq[i][1]);
                    if (xg) mma16816(c[4], wg[i][4], bq[i][0], bq[i][1]);
                }
            }
        };
        have0 = false;
        gather576(scr + (G_X1 + (g % NREP) * 288), sm + SM_AVB, warp, lane,
                  [&] { if (!have0 && landed(bars, CH_GA, 12, lane)) { load_gu(0, 3); have0 = true; } });
        STAMPT(0, 39);
        cbar();
        STAMP0(11);
        uint32_t bq[5][2];
        {
            const uint32_t fo = bfrag + warp * 32;
#pragma unroll
            for (int i = 0; i < 5; i++) { bq[i][0] = lds32(sm + SM_AVB + fo + i * 256); bq[i][1] = lds32(sm + SM_AVB + fo + i * 256 + 16); }
            const uint32_t piv2 = lane < 16 ? 0u : __byte_perm(lds32(sm + SM_AVB + ((lane >> 2) & 3) * AV_PITCH), 0, 0x1010);
            float m0[4] = {0.f, 0.f, 0.f, 0.f}, m1[4] = {0.f, 0.f, 0.f, 0.f};
#pragma unroll
            for (int i = 0; i < 5; i++) {
                uint32_t d[4] = {sub2(bq[i][0], piv2), 0x3F803F80u, sub2(bq[i][1], piv2), 0x3F803F80u};
                if (i == 4 && four) d[0] = d[2] = 0;
                mma16816((i & 1) ? m1 : m0, d, d[0], d[2]);
            }
            if ((lane & 3) == (lane >> 3))
                sts64(sm + SM_RED + (lane >> 2) * 80 + warp * 8, __float_as_uint((lane & 4) ? m0[3] + m1[3] : m0[2] + m1[2]),
                      __float_as_uint((lane & 4) ? m0[1] + m1[1] : m0[0] + m1[0]));
            cbar();
            const uint32_t ra = sm + SM_RED + (lane >> 2) * 80;
            const float4 p0 = lds128f(ra), p1 = lds128f(ra + 16), p2 = lds128f(ra + 32), p3 = lds128f(ra + 48);
            const float sd = (((p0.x + p0.z) + (p1.x + p1.z)) + ((p2.x + p2.z) + (p3.x + p3.z))) * (1.0f / D_MODEL);
            const float sq = ((p0.y + p0.w) + (p1.y + p1.w)) + ((p2.y + p2.w) + (p3.y + p3.w));
            float mean = bf_hi(piv2) + sd, var = fmaf(sq, 1.0f / D_MODEL, -sd * sd);
            const float mean_o = __shfl_xor_sync(0xffffffffu, mean, 16), var_o = __shfl_xor_sync(0xffffffffu, var, 16);
            uint32_t c1[5][2], sb[5][2];
#pragma unroll
            for (int i = 0; i < 5; i++) {
                c1[i][0] = lds32(sm + SM_CB1 + fo + i * 256); c1[i][1] = lds32(sm + SM_CB1 + fo + i * 256 + 16);
                sb[i][0] = lds32(sm + SM_SB + fo + i * 256); sb[i][1] = lds32(sm + SM_SB + fo + i * 256 + 16);
            }
            have1 = mbar_test(bars + (CH_GB + min(lane, 5)) * 8);
            const float mean_r = lane < 16 ? mean : mean_o, var_r = lane < 16 ? var : var_o;
            if ((mean_r * mean_r > 16.0f * var_r) == (lane < 16)) { mean = mean_o; var = var_o; }
            const float mean_b = bfr(mean), rden = ln_rden(var);
            STAMPT(0, 40);
            const uint32_t mean2 = __byte_perm(__float_as_uint(mean_b), 0, 0x3232);
#pragma unroll
            for (int i = 0; i < 5; i++) {
                bq[i][0] = ln_mod2(bq[i][0], mean2, rden, c1[i][0], sb[i][0]);
                bq[i][1] = ln_mod2(bq[i][1], mean2, rden, c1[i][1], sb[i][1]);
            }
        }
        STAMPT(0, 12);
        {
            float c[5][4];
#pragma unroll
            for (int u = 0; u < 5; u++) { c[u][0] = c[u][1] = c[u][2] = c[u][3] = 0.f; }
            if (!have0) { wait_landed(bars, CH_GA, 12, lane); load_gu(0, 3); }
            have1 = __all_sync(0xffffffffu, have1);
            if (have1) load_gu(3, 5);
            mma_gu(c, bq, 0, 3);
            STAMPT(0, 42);
            if (!have1) { wait_landed(bars, CH_GB, 6, lane); load_gu(3, 5); }
            mma_gu(c, bq, 3, 5);
            STAMPT(0, 43);
            const bool t1 = (lane & 2) != 0;
            const uint32_t rb = sm + SM_GRED + warp * 1280 + ((lane >> 2) * 2 + (lane & 1)) * 16;
#pragma unroll
            for (int u = 0; u < 4; u += 2)
                sts128f(rb + (t1 ? 256 : 0) + u * 256, t1 ? c[u + 1][0] : c[u][0], t1 ? c[u + 1][1] : c[u][1], t1 ? c[u + 1][2] : c[u][2], t1 ? c[u + 1][3] : c[u][3]);
            sts128f(rb + 1024, c[4][0], c[4][1], c[4][2], c[4][3]);
        }
        STAMPT(0, 44);
        if (tid >= 160) {
            cbar();
            const int t = tid - 160;
            float4 r = sum8(sm + SM_GRED + min(t, 79) * 16, 1280);
            if ((g & 1) == 0) { r.x = gelu(bfr(r.x)); r.y = gelu(bfr(r.y)); r.z = gelu(bfr(r.z)); r.w = gelu(bfr(r.w)); }
            uint32_t* dst = scr32 + (G_ACT * 4 + (g & 1) * 9216 + (t < 64 ? f0 * 2 + (t >> 4) * 32 : fx * 2) + (t & 15));
            pub32(t < (xg ? 80 : 64), dst, enc(pack_bf(r.x, r.y)));
            pub32(t < (xg ? 80 : 64), dst + 16, enc(pack_bf(r.z, r.w)));
            STAMPT(160, 13);
            static_assert(G_Q - G_H <= NCTA * 32, "clear split");
            clr128(t < 32 && G_H + cta * 32 + t < G_Q, scr + (G_H + cta * 32 + t));
        } else {
            asm volatile("bar.arrive 1, 256;" ::: "memory");
            have0 = have1 = false;
            uint4 v[2];
            const int t = min(tid, 143);
            poll<2, SLP_A, false>(v, scr + (G_ACT + g * 144 + t), 2304, 0,
                                  [&] { if (!have1) proj_load(1, __ballot_sync(0xffffffffu, mbar_test(proj_bar(1)))); });
            put_piece(make_uint4(~mul2(~v[0].x, ~v[1].x), ~mul2(~v[0].y, ~v[1].y), ~mul2(~v[0].z, ~v[1].z), ~mul2(~v[0].w, ~v[1].w)),
                      sm + SM_AVA + t * 4);
        }
    }
    }
}

typedef CUresult (*EncodeFn)(CUtensorMap*, CUtensorMapDataType, cuuint32_t, void*, const cuuint64_t*, const cuuint64_t*,
                             const cuuint32_t*, const cuuint32_t*, CUtensorMapInterleave, CUtensorMapSwizzle,
                             CUtensorMapL2promotion, CUtensorMapFloatOOBfill);

void make3d(EncodeFn fn, CUtensorMap* m, const void* p, uint64_t d0, uint64_t d1, uint64_t d2, uint64_t s1, uint64_t s2,
            uint32_t b0, uint32_t b1, uint32_t b2, CUtensorMapSwizzle sw, CUtensorMapL2promotion promo) {
    cuuint64_t gd[3] = {d0, d1, d2};
    cuuint64_t gs[2] = {s1, s2};
    cuuint32_t bx[3] = {b0, b1, b2};
    cuuint32_t es[3] = {1, 1, 1};
    fn(m, CU_TENSOR_MAP_DATA_TYPE_BFLOAT16, 3, const_cast<void*>(p), gd, gs, bx, es, CU_TENSOR_MAP_INTERLEAVE_NONE, sw, promo,
       CU_TENSOR_MAP_FLOAT_OOB_FILL_NONE);
}

}

extern "C" void kernel_launch(void* const* d_in, const int* in_sizes, int n_in, void* d_out, int out_size) {
    (void)in_sizes; (void)n_in; (void)out_size;
    EncodeFn fn = nullptr;
    cudaDriverEntryPointQueryResult qr;
    cudaGetDriverEntryPoint("cuTensorMapEncodeTiled", (void**)&fn, cudaEnableDefault, &qr);
    cudaFuncSetAttribute(fused_block_kernel, cudaFuncAttributeMaxDynamicSharedMemorySize, SM_LAUNCH);
    Params prm;
#define WPROMO CU_TENSOR_MAP_L2_PROMOTION_L2_128B
    const CUtensorMapL2promotion P128 = WPROMO, P256 = KVPROMO;
    make3d(fn, &prm.m[M_K], d_in[1], 64, (uint64_t)NB * 16 * SK, 2, 256, 128, 64, 64, 2, CU_TENSOR_MAP_SWIZZLE_128B, P256);
    make3d(fn, &prm.m[M_V], d_in[2], 64, (uint64_t)NB * 16 * SK, 2, 256, 128, 64, 64, 2, CU_TENSOR_MAP_SWIZZLE_128B, P256);
    make3d(fn, &prm.m[M_WMOD], d_in[10], D_MODEL, D_MODEL, 6, 6 * D_MODEL * 2, D_MODEL * 2, 16, 192, 2, CU_TENSOR_MAP_SWIZZLE_32B, P128);
    make3d(fn, &prm.m[M_WQ], d_in[3], 4096, D_MODEL, 1, 8192, 8192 * D_MODEL, 32, 192, 1, CU_TENSOR_MAP_SWIZZLE_64B, P128);
    for (int x = 0; x < 2; x++) {
        const CUtensorMapSwizzle sp = x ? CU_TENSOR_MAP_SWIZZLE_32B : CU_TENSOR_MAP_SWIZZLE_128B;
        make3d(fn, &prm.m[M_WO + 4 * x], d_in[4], D_MODEL, 4096, 1, D_MODEL * 2, D_MODEL * 2 * 4096, x ? 16 : 64, x ? 128 : 64, 1, sp, P128);
        make3d(fn, &prm.m[M_WD + 4 * x], d_in[8], D_MODEL, FF, 1, D_MODEL * 2, D_MODEL * 2 * FF, x ? 16 : 64, x ? 144 : 48, 1, sp, P128);
        make3d(fn, &prm.m[M_WG + 4 * x], d_in[6], FF, D_MODEL, 1, FF * 2, FF * 2 * D_MODEL, x ? 16 : 64, x ? 192 : 48, 1, sp, P128);
        make3d(fn, &prm.m[M_WU + 4 * x], d_in[7], FF, D_MODEL, 1, FF * 2, FF * 2 * D_MODEL, x ? 16 : 64, x ? 192 : 48, 1, sp, P128);
    }
    void* scr = nullptr;
    void* plan = nullptr;
    cudaGetSymbolAddress(&scr, g_scr);
    cudaGetSymbolAddress(&plan, g_plan);
    fused_block_kernel<<<NCTA, NTHREADS, SM_LAUNCH>>>(prm, (const __nv_bfloat16*)d_in[0], (const __nv_bfloat16*)d_in[9],
                                                     (__nv_bfloat16*)d_out, (uint4*)scr, plan);
}
```

```cpp
#include <cuda_runtime.h>
#include <cuda_bf16.h>
#include <cuda.h>
#include <stdint.h>
#include <stdlib.h>

namespace {

constexpr int D_MODEL = 576;
constexpr int NB = 4;
constexpr int SK = 4096;
constexpr int FF = 4608;
constexpr int NCTA = 128;
constexpr int NTHREADS = 320;
constexpr int NSLOT = 12;
constexpr int TILE_BYTES = 16384;
constexpr int TILES = 32;
constexpr int AV_PITCH = 1168;

constexpr int SM_W0 = 7 * TILE_BYTES;
constexpr int SM_X = 4 * TILE_BYTES;
constexpr int SM_WO = SM_X + 36864;
constexpr int SM_WG = SM_WO + 32768;
constexpr int SM_WD = 12288;
constexpr int SM_GRED = 3 * TILE_BYTES;
constexpr int SM_SC = NSLOT * TILE_BYTES;
constexpr int SM_RED = SM_SC + 8192;
constexpr int SM_AVA = SM_RED + 4096;
constexpr int SM_AVB = SM_AVA + 4 * AV_PITCH;
constexpr int SM_CB1 = SM_AVB + 4 * AV_PITCH;
constexpr int SM_SB = SM_CB1 + 4 * AV_PITCH;
constexpr int SM_QS = SM_SB + 4 * AV_PITCH;
constexpr int SM_XR = SM_QS + 512;
constexpr int SM_BAR = SM_XR + 64;
constexpr int CH_KV = 6, CH_WO = 70, CH_GA = 76, CH_GB = 88, CH_WD = 94, NCHUNK = 100;
constexpr int REL = NCHUNK, RELW = REL + 64, NBAR = RELW + 2;
constexpr int SM_TAB = SM_BAR + 1360;
static_assert(NBAR * 8 <= 1360, "bars");
constexpr int SM_ADJ = SM_TAB + NCHUNK * 16;
constexpr int SM_ORG = SM_ADJ + 16;
constexpr int SM_TOTAL = SM_ORG + 96;
static_assert(SM_TOTAL <= 232448, "smem");
#define NB_ 1
constexpr int NBURST = NB_;
__host__ __device__ constexpr int slot_of(int i) { return i % NSLOT; }

#define EVF 2
#define NHARD 4
#define HARD_WAIT 0x546
#define KFIRST 36
#define WQ_FREE 0
#define KVPROMO CU_TENSOR_MAP_L2_PROMOTION_L2_256B
#define SLP 40
#define PACE_SLEEP 0
#define SLP_X 0
#define SLP_A 0
#define PFMAP 1
#define MODAT (4 + cta % 3)
#define GATE_X false
#define GU_MID 1
#define SLP_GATE 300
#define GATE_MASK 0
#define SLP_R 0
#define SLP_O 0

constexpr unsigned SPIN_LIMIT = 1u << 22;
constexpr float LOG2E = 1.4426950408889634f;

enum { M_K = 0, M_V, M_WMOD, M_WQ, M_WO, M_WD, M_WG, M_WU, M_WOX, M_WDX, M_WGX, M_WUX, NMAPS };
struct alignas(16) Plan { uint32_t e[128][4]; };
struct Params { CUtensorMap m[NMAPS]; };

constexpr int knob(const char*, int dflt) { return dflt; }
#define PLAN_CONST constexpr

PLAN_CONST Plan make_plan() {
    Plan pl = {};
    const int main_from = knob("MAIN_FROM", 13);
    const int win_start = knob("WIN_START", 48), win_main = knob("WIN_MAIN", 64), win_last = knob("WIN_LAST", 64), n_last = knob("N_LAST", 0);
    const int win_wo = knob("WIN_WO", 44), win_gu = knob("WIN_GU", 48), win_wd = knob("WIN_WD", 32);
    const int lo_main = knob("LO_MAIN", 32), hi_main = knob("HI_MAIN", 32), lag_main = knob("LAG_MAIN", 56);
    const int lo_tail = knob("LO_TAIL", 6), hi_tail = knob("HI_TAIL", 6), lag_tail = knob("LAG_TAIL", 16);
    const int lo_last = knob("LO_LAST", 16), hi_last = knob("HI_LAST", 16), lag_last = knob("LAG_LAST", 32);
    int cum = 0;
    const unsigned char tail[30] = {70, 74, 71, 75, 72, 73, 76, 77, 84, 85, 78, 79, 80, 81, 86, 87, 82, 83,
                                           88, 89, 92, 93, 90, 91, 94, 95, 96, 97, 98, 99};
    int order[NCHUNK] = {}, n = 0, w = 0, last_tile = 0;
    for (int i = 0; i < 3; i++) order[n++] = i;
    for (int i = 0; i < NBURST; i++) order[n++] = CH_KV + i;
    for (int i = 3; i < 6; i++) order[n++] = i;
    for (int i = NBURST; i < 2 * TILES; i++) {
        last_tile = n;
        order[n++] = CH_KV + i;
    }
    while (w < 30) order[n++] = tail[w++];
    int last_user[NSLOT] = {};
    for (int i = 0; i < NSLOT; i++) last_user[i] = i >= 9 ? RELW + 1 : i >= 7 ? RELW : 0;
    int bytes_at[NCHUNK] = {};
    for (int p = 0; p < NCHUNK; p++) {
        const int c = order[p];
        const int x = c == 74 || c == 75 ? c - 74 : c >= 84 && c < 88 ? c - 82 : c == 92 || c == 93 ? c - 86 : -1;
        int map = 0, dst = 0, row = 0, bytes = 0;
        if (c < CH_KV) { map = c < 3 ? M_WMOD : M_WQ; dst = SM_W0 + c * 12288; bytes = 12288; row = (c % 3) * 192; }
        else if (c < CH_WO) { const int i = c - CH_KV; map = i / TILES; dst = slot_of(i) * TILE_BYTES; bytes = TILE_BYTES; row = (i % TILES) * 128; }
        else if (x >= 0) { map = 0; dst = SM_X; bytes = 0; row = x; }
        else if (c < CH_GA) { const int t = c - CH_WO; map = M_WO; dst = SM_WO + t * 8192; bytes = 8192; row = t * 64; }
        else if (c < CH_WD) { const int t = c < CH_GB ? c - CH_GA : c - CH_GB + 8; map = M_WG; dst = t < 10 ? SM_WG + t * 6144 : (t - 10) * 6144; bytes = 6144; row = t * 48; }
        else { const int t = c - CH_WD; map = M_WD; dst = SM_WD + t * 6144; bytes = 6144; row = t * 48; }
        bytes_at[p] = bytes ? bytes : 2048;
        unsigned rel = 0, wait = 0;
        if (x >= 0) rel = last_user[4] | (last_user[5] << 8);
        else if (c >= CH_KV) rel = last_user[dst / TILE_BYTES] | (last_user[(dst + bytes - 1) / TILE_BYTES] << 8);
        if (c >= CH_KV && c < CH_WO) last_user[dst / TILE_BYTES] = REL + c - CH_KV;
        const int win = p < main_from ? win_start : p <= last_tile - n_last ? win_main : p <= last_tile ? win_last
                      : c < CH_GA ? win_wo : c < CH_WD ? win_gu : win_wd;
        const bool tl = p > last_tile, ls = p > last_tile - n_last;
        cum += bytes_at[p] / 1024;
        for (int k = 0; k < 2; k++) {
            const int lim = (p < main_from ? win : k ? win - (tl ? lo_tail : ls ? lo_last : lo_main) : win + (tl ? hi_tail : ls ? hi_last : hi_main)) * 1024;
            int q = p - 1, sum = bytes_at[p];
            while (q > 0 && (sum + bytes_at[q] <= lim || bytes_at[q] == 2048)) sum += bytes_at[q--];
            wait |= (unsigned)order[q < 0 ? 0 : q] << (8 * k);
        }
        const int thr = cum - win - (tl ? lag_tail : ls ? lag_last : lag_main);
        wait = rel | (wait << 16);
        rel = (unsigned)(thr < 0 ? 0 : thr) | ((unsigned)cum << 18);
        pl.e[p][0] = dst | (map << 20) | (c << 24); pl.e[p][1] = row | (bytes << 16); pl.e[p][2] = rel; pl.e[p][3] = wait;
    }
    return pl;
}
__device__ const Plan g_plan = make_plan();

#define NREP_ 4
constexpr int NREP = NREP_;
constexpr int G_CNT = 0;
constexpr int G_H = G_CNT + 8;
constexpr int G_MOD = G_H + NREP * 288;
constexpr int G_Q = G_MOD + 1152;
constexpr int G_STAT = G_Q + 2048;
constexpr int G_OPART = G_STAT + NCTA * 8;
constexpr int G_X1 = G_OPART + 4 * NCTA * 64;
constexpr int G_ACT = G_X1 + NREP * 288;
constexpr int G_PART = G_ACT + 2 * 2304;
constexpr int G_TOTAL = G_PART + 2 * 72 * 128;
__device__ __align__(128) uint4 g_scr[G_TOTAL];
#define STAMP(i)
#define STAMPT(t, i)
#define STAMP0(i)
constexpr int SM_LAUNCH = SM_TOTAL;

__device__ __forceinline__ uint32_t enc(uint32_t w) { return max(~w, 1u); }
__device__ __forceinline__ uint32_t encf(float f) { return enc(__float_as_uint(f)); }
__device__ __forceinline__ float decf(uint32_t w) { return __uint_as_float(~w); }
__device__ __forceinline__ float bf_lo(uint32_t w) { return __uint_as_float(w << 16); }
__device__ __forceinline__ float bf_hi(uint32_t w) { return __uint_as_float(w & 0xFFFF0000u); }
__device__ __forceinline__ uint32_t pack_bf(float lo, float hi) {
    uint32_t r;
    asm("cvt.rn.bf16x2.f32 %0, %1, %2;" : "=r"(r) : "f"(hi), "f"(lo));
    return r;
}
__device__ __forceinline__ float bfr(float x) { return __uint_as_float(pack_bf(0.f, x)); }
__device__ __forceinline__ uint32_t mul2(uint32_t a, uint32_t b) { uint32_t r; asm("mul.rn.bf16x2 %0, %1, %2;" : "=r"(r) : "r"(a), "r"(b)); return r; }
__device__ __forceinline__ uint32_t add2(uint32_t a, uint32_t b) { uint32_t r; asm("add.rn.bf16x2 %0, %1, %2;" : "=r"(r) : "r"(a), "r"(b)); return r; }
__device__ __forceinline__ uint32_t sub2(uint32_t a, uint32_t b) { uint32_t r; asm("sub.rn.bf16x2 %0, %1, %2;" : "=r"(r) : "r"(a), "r"(b)); return r; }
__device__ __forceinline__ float ex2(float x) { float r; asm("ex2.approx.ftz.f32 %0, %1;" : "=f"(r) : "f"(x)); return r; }
__device__ __forceinline__ float rcp(float x) { float r; asm("rcp.approx.ftz.f32 %0, %1;" : "=f"(r) : "f"(x)); return r; }
__device__ __forceinline__ float fsqrt(float x) { float r; asm("sqrt.approx.ftz.f32 %0, %1;" : "=f"(r) : "f"(x)); return r; }
__device__ __forceinline__ float sigm(float x) { return rcp(1.0f + ex2(-LOG2E * x)); }
__device__ __forceinline__ float gelu(float g) { return g * sigm(1.5957691216057308f * (g + 0.044715f * g * g * g)); }
__device__ __forceinline__ void mbar_init(uint32_t bar, uint32_t cnt) {
    asm volatile("mbarrier.init.shared::cta.b64 [%0], %1;" ::"r"(bar), "r"(cnt) : "memory");
}
__device__ __forceinline__ void mbar_expect(uint32_t bar, uint32_t bytes) {
    asm volatile("mbarrier.arrive.expect_tx.shared::cta.b64 _, [%0], %1;" ::"r"(bar), "r"(bytes) : "memory");
}
__device__ __forceinline__ void mbar_arrive(uint32_t bar) {
    asm volatile("mbarrier.arrive.shared::cta.b64 _, [%0];" ::"r"(bar) : "memory");
}
__device__ __forceinline__ void mbar_wait(uint32_t bar) {
    asm volatile("{\n.reg .pred p;\n.reg .u32 n;\nmov.u32 n, 0;\n"
                 "W_%=:\nmbarrier.try_wait.parity.shared::cta.b64 p, [%0], 0;\n@p bra D_%=;\n"
                 "add.u32 n, n, 1;\nsetp.lt.u32 p, n, %1;\n@p bra W_%=;\ntrap;\nD_%=:\n}"
                 ::"r"(bar), "n"(SPIN_LIMIT) : "memory");
}
__device__ __forceinline__ bool mbar_test(uint32_t bar) {
    uint32_t ok;
    asm volatile("{\n.reg .pred p;\nmbarrier.test_wait.parity.shared::cta.b64 p, [%1], 0;\nselp.u32 %0, 1, 0, p;\n}" : "=r"(ok) : "r"(bar) : "memory");
    return ok != 0;
}
__device__ __forceinline__ void tma3(uint32_t dst, const CUtensorMap* m, int c0, int c1, int c2, uint32_t bar, uint64_t pol) {
    asm volatile("cp.async.bulk.tensor.3d.shared::cluster.global.mbarrier::complete_tx::bytes.L2::cache_hint [%0], [%1, {%3, %4, %5}], [%2], %6;"
                 ::"r"(dst), "l"(m), "r"(bar), "r"(c0), "r"(c1), "r"(c2), "l"(pol) : "memory");
}
__device__ __forceinline__ void cbar() { asm volatile("bar.sync 1, 256;" ::: "memory"); }
__device__ __forceinline__ void ldsm4(uint32_t (&r)[4], uint32_t a) {
    asm volatile("ldmatrix.sync.aligned.m8n8.x4.shared.b16 {%0,%1,%2,%3}, [%4];"
                 : "=r"(r[0]), "=r"(r[1]), "=r"(r[2]), "=r"(r[3]) : "r"(a) : "memory");
}
__device__ __forceinline__ void ldsm4t(uint32_t (&r)[4], uint32_t a) {
    asm volatile("ldmatrix.sync.aligned.m8n8.x4.trans.shared.b16 {%0,%1,%2,%3}, [%4];"
                 : "=r"(r[0]), "=r"(r[1]), "=r"(r[2]), "=r"(r[3]) : "r"(a) : "memory");
}
__device__ __forceinline__ void mma16816(float (&c)[4], const uint32_t (&a)[4], uint32_t b0, uint32_t b1) {
    asm volatile("mma.sync.aligned.m16n8k16.row.col.f32.bf16.bf16.f32 {%0,%1,%2,%3}, {%4,%5,%6,%7}, {%8,%9}, {%0,%1,%2,%3};"
                 : "+f"(c[0]), "+f"(c[1]), "+f"(c[2]), "+f"(c[3])
                 : "r"(a[0]), "r"(a[1]), "r"(a[2]), "r"(a[3]), "r"(b0), "r"(b1));
}
__device__ __forceinline__ uint32_t lds32(uint32_t a) {
    uint32_t r; asm volatile("ld.shared.b32 %0, [%1];" : "=r"(r) : "r"(a) : "memory"); return r;
}
__device__ __forceinline__ uint32_t lds16(uint32_t a) {
    unsigned short r; asm volatile("ld.shared.b16 %0, [%1];" : "=h"(r) : "r"(a) : "memory"); return r;
}
__device__ __forceinline__ float ldsf(uint32_t a) { return __uint_as_float(lds32(a)); }
__device__ __forceinline__ uint4 lds128(uint32_t a) {
    uint4 r; asm volatile("ld.shared.v4.b32 {%0,%1,%2,%3}, [%4];" : "=r"(r.x), "=r"(r.y), "=r"(r.z), "=r"(r.w) : "r"(a) : "memory"); return r;
}
__device__ __forceinline__ float4 lds128f(uint32_t a) {
    float4 r; asm volatile("ld.shared.v4.f32 {%0,%1,%2,%3}, [%4];" : "=f"(r.x), "=f"(r.y), "=f"(r.z), "=f"(r.w) : "r"(a) : "memory"); return r;
}
__device__ __forceinline__ void sts16(uint32_t a, uint32_t v) { asm volatile("st.shared.b16 [%0], %1;" ::"r"(a), "h"((unsigned short)v) : "memory"); }
__device__ __forceinline__ void sts32(uint32_t a, uint32_t v) { asm volatile("st.shared.b32 [%0], %1;" ::"r"(a), "r"(v) : "memory"); }
__device__ __forceinline__ void sts64(uint32_t a, uint32_t x, uint32_t y) { asm volatile("st.shared.v2.b32 [%0], {%1,%2};" ::"r"(a), "r"(x), "r"(y) : "memory"); }
__device__ __forceinline__ void stsf(uint32_t a, float v) { sts32(a, __float_as_uint(v)); }
__device__ __forceinline__ void sts128(uint32_t a, uint4 v) {
    asm volatile("st.shared.v4.b32 [%0], {%1,%2,%3,%4};" ::"r"(a), "r"(v.x), "r"(v.y), "r"(v.z), "r"(v.w) : "memory");
}
__device__ __forceinline__ void sts128f(uint32_t a, float x, float y, float z, float w) {
    asm volatile("st.shared.v4.f32 [%0], {%1,%2,%3,%4};" ::"r"(a), "f"(x), "f"(y), "f"(z), "f"(w) : "memory");
}
__device__ __forceinline__ float4 sum8(uint32_t a, int st) {
    float4 v[8];
#pragma unroll
    for (int w = 0; w < 8; w++) v[w] = lds128f(a + w * st);
#pragma unroll
    for (int o = 4; o; o >>= 1)
#pragma unroll
        for (int w = 0; w < o; w++) { v[w].x += v[w + o].x; v[w].y += v[w + o].y; v[w].z += v[w + o].z; v[w].w += v[w + o].w; }
    return v[0];
}
__device__ __forceinline__ void pub32(bool p, void* a, uint32_t v) {
    asm volatile("{\n.reg .pred q;\nsetp.ne.u32 q, %2, 0;\n@q st.relaxed.gpu.global.b32 [%0], %1;\n}" ::"l"(a), "r"(v), "r"((uint32_t)p) : "memory");
}
__device__ __forceinline__ void pub64(bool p, void* a, uint32_t x, uint32_t y) {
    asm volatile("{\n.reg .pred q;\nsetp.ne.u32 q, %3, 0;\n@q st.relaxed.gpu.global.v2.b32 [%0], {%1,%2};\n}" ::"l"(a), "r"(x), "r"(y), "r"((uint32_t)p) : "memory");
}
__device__ __forceinline__ void st16(bool p, void* a, uint32_t v) {
    asm volatile("{\n.reg .pred q;\nsetp.ne.u32 q, %2, 0;\n@q st.global.b16 [%0], %1;\n}" ::"l"(a), "h"((unsigned short)v), "r"((uint32_t)p) : "memory");
}
__device__ __forceinline__ void clr128(bool p, void* a) {
    asm volatile("{\n.reg .pred q;\nsetp.ne.u32 q, %1, 0;\n@q st.relaxed.gpu.global.v4.b32 [%0], {%2,%2,%2,%2};\n}" ::"l"(a), "r"((uint32_t)p), "r"(0) : "memory");
}
__device__ __forceinline__ uint32_t back32(bool p, const void* a) {
    uint32_t r = 0;
    asm volatile("{\n.reg .pred q;\nsetp.ne.u32 q, %2, 0;\n@q ld.relaxed.gpu.global.b32 %0, [%1];\n}" : "+r"(r) : "l"(a), "r"((uint32_t)p) : "memory");
    return r;
}
__device__ __forceinline__ void ldg_missing(uint4& r, const uint4* p, uint32_t lo) {
    asm volatile("{\n.reg .pred q;\nsetp.eq.u32 q, %5, 0;\n@q ld.relaxed.gpu.global.v4.b32 {%0,%1,%2,%3}, [%4];\n}"
                 : "+r"(r.x), "+r"(r.y), "+r"(r.z), "+r"(r.w) : "l"(p), "r"(lo) : "memory");
}
__device__ __forceinline__ uint32_t min4(const uint4& v) { return min(min(v.x, v.y), min(v.z, v.w)); }
template <int N, int SLEEP, bool GATE, class Side>
__device__ __forceinline__ void poll(uint4 (&v)[N], const uint4* p, int stride, uint32_t skip, Side side) {
    uint32_t lo[N];
#pragma unroll
    for (int i = 0; i < N; i++) { lo[i] = (skip >> i) & 1; v[i] = make_uint4(lo[i], lo[i], lo[i], lo[i]); }
    uint32_t hold0 = GATE ? threadIdx.x & GATE_MASK : 0, hold = GATE;
#pragma unroll 1
    for (unsigned it = 0;; it++) {
#pragma unroll
        for (int i = 0; i < N; i++) ldg_missing(v[i], p + i * stride, lo[i] | (i ? hold : hold0));
        side();
        uint32_t all = 0xFFFFFFFFu;
#pragma unroll
        for (int i = 0; i < N; i++) { lo[i] = min4(v[i]); all = min(all, lo[i]); }
        if (__all_sync(0xffffffffu, all != 0)) break;
        if (it > SPIN_LIMIT) __trap();
        if (GATE && hold) {
            if (__any_sync(0xffffffffu, lo[0] != 0)) hold0 = hold = 0; else __nanosleep(SLP_GATE);
        } else if (SLEEP) __nanosleep(SLEEP);
    }
}
template <int N, int SLEEP>
__device__ __forceinline__ void poll(uint4 (&v)[N], const uint4* p, int stride) { poll<N, SLEEP, false>(v, p, stride, 0, [] {}); }
__device__ __forceinline__ uint4 unzip(const uint4& e) {
    uint4 r;
    r.x = ~__byte_perm(e.x, e.z, 0x5410);
    r.y = ~__byte_perm(e.x, e.z, 0x7632);
    r.z = ~__byte_perm(e.y, e.w, 0x5410);
    r.w = ~__byte_perm(e.y, e.w, 0x7632);
    return r;
}
__device__ __forceinline__ void put_piece(const uint4& e, uint32_t a) {
    const uint4 u = unzip(e);
    sts32(a, u.x); sts32(a + AV_PITCH, u.y); sts32(a + 2 * AV_PITCH, u.z); sts32(a + 3 * AV_PITCH, u.w);
}
template <int SLEEP, bool GATE, class Side>
__device__ __forceinline__ void gather576(const uint4* src, uint32_t dst, int warp, int lane, Side side) {
    uint4 v[2];
    const int t = warp * 36 + lane;
    poll<2, SLEEP, GATE>(v, src + t, 32, lane < 4 ? 0 : 2, side);
    put_piece(v[0], dst + t * 4);
    if (lane < 4) put_piece(v[1], dst + t * 4 + 128);
}
__device__ __forceinline__ float ln_rden(float var) { return rcp(bfr(fsqrt(bfr(bfr(fmaxf(var, 0.f)) + 1e-5f)))); }
__device__ __forceinline__ void ln_stats(const uint32_t (&w)[9], float& mean_b, float& rden) {
    const float piv = __shfl_sync(0xffffffffu, bf_lo(w[0]), 0);
    float s = 0.f, q = 0.f;
#pragma unroll
    for (int i = 0; i < 9; i++) {
        const float a = bf_lo(w[i]) - piv, c = bf_hi(w[i]) - piv;
        s += a + c;
        q = fmaf(a, a, fmaf(c, c, q));
    }
#pragma unroll
    for (int o = 16; o; o >>= 1) { s += __shfl_xor_sync(0xffffffffu, s, o); q += __shfl_xor_sync(0xffffffffu, q, o); }
    s *= (1.0f / D_MODEL);
    mean_b = bfr(piv + s);
    rden = ln_rden(fmaf(q, 1.0f / D_MODEL, -s * s));
}
__device__ __forceinline__ float ln_mod(float x, float mean_b, float rden, float scale1, float shift) {
    return bfr(bfr(bfr(x - mean_b) * rden) * scale1) + shift;
}

__device__ __forceinline__ uint32_t ln_mod2(uint32_t x, uint32_t mean2, float rden, uint32_t scale1, uint32_t shift) {
    const uint32_t d = sub2(x, mean2);
    return add2(mul2(pack_bf(bf_lo(d) * rden, bf_hi(d) * rden), scale1), shift);
}

__global__ void __launch_bounds__(NTHREADS, 1)
fused_block_kernel(const __grid_constant__ Params prm, const __nv_bfloat16* __restrict__ x, const __nv_bfloat16* __restrict__ cvec,
                   __nv_bfloat16* __restrict__ out, uint4* __restrict__ scr, const void* __restrict__ plan) {
    extern __shared__ __align__(1024) unsigned char smem_raw[];
    const uint32_t sm = (uint32_t)__cvta_generic_to_shared(smem_raw);
    const uint32_t bars = sm + SM_BAR;
    const int tid = threadIdx.x, warp = __shfl_sync(0xffffffffu, tid >> 5, 0), lane = tid & 31;
    const int cta = blockIdx.x;
    const int g = cta >> 3, j = cta & 7;
    const int f0 = (g >> 1) * 576 + j * 64, fx = (g >> 1) * 576 + 448 + j * 16;
    const bool xg = j >= 4;

    auto kv_row = [&](int n) { return ((n >> 3) * 16 + g) * SK + ((n & 7) * 8 + j) * 64; };
    if (warp >= 8) {
    if (warp == 8) {
        uint64_t pol_kv, pol_w;
        asm volatile("createpolicy.fractional.L2::evict_first.b64 %0, 1.0;" : "=l"(pol_kv));
        asm volatile("createpolicy.fractional.L2::evict_normal.b64 %0, 1.0;" : "=l"(pol_w));
        if (!EVF) pol_kv = pol_w;
        if (EVF == 2) pol_w = pol_kv;
        if (lane == 0) {
#pragma unroll
            for (int n = 0; n < 6 + NBURST; n++) if (n < 3 || n >= 6) mbar_init(bars + n * 8, 1);
            asm volatile("fence.mbarrier_init.release.cluster;" ::: "memory");
            auto burst = [&]() {
#pragma unroll
                for (int n = 0; n < NBURST; n++) {
                    mbar_expect(bars + (CH_KV + n) * 8, TILE_BYTES);
                    tma3(sm + n * TILE_BYTES, &prm.m[M_K], 0, kv_row(n), 0, bars + (CH_KV + n) * 8, pol_kv);
                }
            };
            if (cta >= KFIRST) burst();
#pragma unroll
            for (int n = 0; n < 3; n++) {
                mbar_expect(bars + n * 8, cta < 108 ? 12288 : 0);
                if (cta < 108) tma3(sm + SM_W0 + n * 12288, &prm.m[M_WMOD], (cta % 36) * 16, n * 192, (cta / 36) * 2, bars + n * 8, pol_w);
            }
            if (cta < KFIRST) burst();
            STAMP(46);
#pragma unroll
            for (int n = 3; n < 12; n++) if (n < 6 || n >= 6 + NBURST) mbar_init(bars + n * 8, 1);
            mbar_init(bars + RELW * 8, 1);
            mbar_init(bars + (RELW + 1) * 8, 1);
            asm volatile("fence.mbarrier_init.release.cluster;" ::: "memory");
        }
        __syncwarp();
        asm volatile("bar.arrive 4, %0;" ::"n"(NTHREADS) : "memory");
        if (lane == 0) {
#pragma unroll 1
            for (int n = 0; n < 3; n++) {
                mbar_expect(bars + (3 + n) * 8, 12288);
                if (n >= WQ_FREE) mbar_wait(bars + (n - WQ_FREE) * 8);
                tma3(sm + SM_W0 + (3 + n) * 12288, &prm.m[M_WQ], cta * 32, n * 192, 0, bars + (3 + n) * 8, pol_w);
            }
#pragma unroll 1
            for (int n = NBURST; n < NHARD; n++) {
                mbar_expect(bars + (CH_KV + n) * 8, TILE_BYTES);
                mbar_wait(bars + ((HARD_WAIT >> (4 * (n - NBURST))) & 15) * 8);
                tma3(sm + n * TILE_BYTES, &prm.m[M_K], 0, kv_row(n), 0, bars + (CH_KV + n) * 8, pol_kv);
            }
        }
        __syncwarp();
        asm volatile("bar.sync 2, 64;" ::: "memory");
        if (sm & 1023) __trap();
        uint4 e = lds128(sm + SM_TAB + (6 + NHARD) * 16);
#pragma unroll 1
        for (int p = 6 + NHARD; p < NCHUNK; p++) {
            const uint4 nx = lds128(sm + SM_TAB + (p + 1) * 16);
            if (e.x & 0x80000u) {
                const uint32_t tb = bars + ((e.w >> ((lane & 3) * 8)) & 255) * 8;
#pragma unroll 1
                for (unsigned it = 0;; it++) {
                    const bool far = lds32(sm + SM_ADJ) >= (e.y >> 16);
                    if (__all_sync(0xffffffffu, mbar_test(tb) || ((lane & 3) == 3 && far))) break;
                    if (it > 16 * SPIN_LIMIT) __trap();
                }
                if (lane == 0) {
                    tma3(sm + (e.x & 0x7FFFF), &prm.m[(e.x >> 20) & 15], e.y & 0xFFFF, e.z & 0x3FFFF, 0, bars + (e.x >> 24) * 8,
                         (e.x & 0xE00000u) ? pol_w : pol_kv);
                }
            }
            e = nx;
        }
    } else if (warp == 9) {
        if (lane < NMAPS)
            sts64(sm + SM_ORG + lane * 8,
                  lane <= M_V ? 0 : lane <= M_WQ ? cta * 32 : lane <= M_WD ? j * 64 : lane <= M_WU ? f0 : lane <= M_WDX ? 512 + j * 16 : fx,
                  (lane & 2) ? 0 : (lane & 1) ? g * 288 : g * 256);
        if (lane == 0) sts32(sm + SM_ADJ, 0);
        uint4 pe[4];
#pragma unroll
        for (int i = 0; i < 4; i++) pe[i] = __ldg(reinterpret_cast<const uint4*>(plan) + min(lane + 32 * i, NCHUNK - 1));
        asm volatile("bar.sync 4, %0;" ::"n"(NTHREADS) : "memory");
#pragma unroll
        for (int i = 0; i < 4; i++) {
            if ((pe[i].y >> 16) == 0) {
                const uint32_t t = pe[i].y, h = t & 1;
                pe[i].x += xg ? ((t >> 1) - 1) * 6144 + (M_WGX << 20) : t < 2 ? h * 4096 + (M_WOX << 20) : 8192 + h * 4608 + (M_WDX << 20);
                pe[i].y = xg ? (t < 2 || h ? 0 : ((t >> 1) - 1) * 192 + (6144 << 16))
                             : t < 2 ? h * 128 + (4096 << 16) : t >= 6 ? h * 144 + (4608 << 16) : 0;
            }
            if (((pe[i].x >> 20) & 3) == 2 && (pe[i].x >> 24) >= CH_WO) pe[i].x += (g & 1) << 20;
            const int p = lane + 32 * i;
            if (p < NCHUNK) {
                const uint32_t org = sm + SM_ORG + ((pe[i].x >> 20) & 15) * 8;
                if (p >= 6 + NHARD) mbar_expect(bars + (pe[i].x >> 24) * 8, pe[i].y >> 16);
                sts128(sm + SM_TAB + p * 16, make_uint4(pe[i].x | ((pe[i].y >> 16) ? 0x80000u : 0u), lds32(org) | (pe[i].z << 16),
                                                        (((pe[i].x >> 20) & 15) <= M_V ? kv_row((pe[i].y & 0xFFFF) >> 7) : lds32(org + 4) + (pe[i].y & 0xFFFF)) | (pe[i].z & 0xFFFC0000u), pe[i].w));
            }
        }
        asm volatile("bar.arrive 2, 64;" ::: "memory");
        __syncwarp();
        if (PFMAP && lane < NMAPS) asm volatile("prefetch.tensormap [%0];" ::"l"(&prm.m[lane]) : "memory");
        if (lane == 0) {
            int n = 0;
            uint32_t kb = 0;
#pragma unroll 1
            for (unsigned it = 0; n < NCHUNK; it++) {
                while (n < NCHUNK && mbar_test(bars + (lds32(sm + SM_TAB + n * 16) >> 24) * 8)) n++;
                const uint32_t now = n == NCHUNK ? 2048 : n ? lds32(sm + SM_TAB + n * 16 - 8) >> 18 : 0;
                sts32(sm + SM_ADJ, (atomicAdd(reinterpret_cast<unsigned*>(scr + G_CNT), now - kb) & 0x3FFFFu) >> 7);
                kb = now;
                if (it > SPIN_LIMIT) __trap();
                if (PACE_SLEEP) __nanosleep(PACE_SLEEP);
            }
        }
    }
    } else {
    uint2 cw[3];
    uint32_t xw[9];
#pragma unroll
    for (int i = 0; i < 3; i++) cw[i] = cta < 108 ? __ldg(reinterpret_cast<const uint2*>(cvec) + min(tid + 256 * i, 575)) : make_uint2(0, 0);
#pragma unroll
    for (int i = 0; i < 9; i++) xw[i] = cta < 36 && warp >= 4 ? __ldg(reinterpret_cast<const uint32_t*>(x) + (warp & 3) * 288 + lane + 32 * i) : 0u;
    clr128(cta < 32 && tid < 64, scr + (G_Q + cta * 64 + tid));
    uint32_t cleared = back32(cta < 32 && tid < 64, scr + (G_Q + cta * 64 + tid));
    if (lane == 0) {
        static_assert(NCHUNK == 12 + 88, "11 chunk barriers and 8 release barriers per warp");
#pragma unroll
        for (int n = 0; n < 11; n++) mbar_init(bars + (12 + warp * 11 + n) * 8, 1);
#pragma unroll
        for (int n = 0; n < 8; n++) mbar_init(bars + (REL + warp * 8 + n) * 8, 2);
        asm volatile("fence.mbarrier_init.release.cluster;" ::: "memory");
    }
    asm volatile("bar.sync 4, %0;" ::"n"(NTHREADS) : "memory");
    const int mi = lane >> 3, r8 = lane & 7;
    const uint32_t bfrag = ((lane >> 2) & 3) * AV_PITCH + (lane & 3) * 4;
    uint32_t* const scr32 = reinterpret_cast<uint32_t*>(scr);
    uint2* const scr64 = reinterpret_cast<uint2*>(scr);
    const int pr = warp >> 1, hf = warp & 1;

#pragma unroll
    for (int i = 0; i < 3; i++) {
        const int p = min(tid + 256 * i, 575);
        const float a0 = bf_lo(cw[i].x), a1 = bf_hi(cw[i].x), a2 = bf_lo(cw[i].y), a3 = bf_hi(cw[i].y);
        sts64(sm + SM_AVA + (p / 144) * AV_PITCH + (p % 144) * 8, pack_bf(a0 * sigm(a0), a1 * sigm(a1)), pack_bf(a2 * sigm(a2), a3 * sigm(a3)));
    }
    if (cta < 36 && warp >= 4) {
        float mean_b, rden;
        ln_stats(xw, mean_b, rden);
        if (lane == 0) sts64(sm + SM_QS + (warp & 3) * 8, __float_as_uint(mean_b), __float_as_uint(rden));
#pragma unroll
        for (int i = 0; i < 9; i++) sts32(sm + SM_CB1 + (warp & 3) * 1152 + (lane + 32 * i) * 4, xw[i]);
    }
    if (cleared) __trap();
    uint32_t mod_lo = 0, mod_hi = 0;
#pragma unroll 1
    for (int it = 0; it < 2; it++) {
        if (it == 1) gather576<0, true>(scr + (G_H + (g % NREP) * 288), sm + SM_AVB, warp, lane, [] {});
        cbar();
        if (cta < 108 || it == 1) {
            STAMP0(1 + 2 * it);
            const int k = (mi >> 1) * 8 + r8;
            const uint32_t base = sm + SM_W0 + (it ? 36864 + k * 64 : (mi & 1) * 6144 + k * 32);
            const uint32_t ch = it ? (((mi & 1) * 2) ^ (r8 >> 1)) : (r8 >> 2);
            const uint32_t a0 = base + (ch << 4), a1 = base + ((ch ^ 1) << 4), kb = it ? 1024 : 512;
            const uint32_t bb = sm + (it ? SM_AVB : SM_AVA) + bfrag + warp * 32;
            float c0[4] = {0.f, 0.f, 0.f, 0.f}, c1[4] = {0.f, 0.f, 0.f, 0.f};
            uint32_t bq[5][2];
#pragma unroll
            for (int i = 0; i < 5; i++) { bq[i][0] = lds32(bb + i * 256); bq[i][1] = lds32(bb + i * 256 + 16); }
            if (warp >= 4) bq[4][0] = bq[4][1] = 0;
#pragma unroll
            for (int i = 0; i < 3; i++) mbar_wait(bars + (it * 3 + i) * 8);
#pragma unroll
            for (int i = 0; i < 5; i++) {
                const int ks = min(warp + 8 * i, 35);
                const int cq = ks / 12;
                const uint32_t off = cq * 12288 + (ks - cq * 12) * kb;
                uint32_t u[4], v[4];
                ldsm4t(u, a0 + off);
                ldsm4t(v, a1 + off);
                mma16816(c0, u, bq[i][0], bq[i][1]);
                mma16816(c1, v, bq[i][0], bq[i][1]);
            }
            const bool t1 = (lane & 2) != 0;
            sts128f(sm + SM_RED + warp * 512 + (t1 ? 256 : 0) + ((lane >> 2) * 2 + (lane & 1)) * 16,
                    t1 ? c1[0] : c0[0], t1 ? c1[1] : c0[1], t1 ? c1[2] : c0[2], t1 ? c1[3] : c0[3]);
            cbar();
            if (warp == 7) {
                const float4 r = sum8(sm + SM_RED + lane * 16, 512);
                if (it == 0 && cta < 36) {
                    const uint32_t xp = sm + SM_CB1 + (lane & 1) * 2304 + (cta * 16 + (lane >> 1)) * 2;
                    const float4 st = lds128f(sm + SM_QS + (lane & 1) * 16);
                    const float h0 = ln_mod(bf_lo(lds16(xp)), st.x, st.y, bfr(1.0f + bfr(r.z)), bfr(r.x));
                    const float h1 = ln_mod(bf_lo(lds16(xp + 1152)), st.z, st.w, bfr(1.0f + bfr(r.w)), bfr(r.y));
                    const uint32_t hv = enc(pack_bf(h0, h1));
#pragma unroll
                    for (int i = 0; i < NREP; i++) pub32(true, scr32 + (G_H * 4 + i * 1152 + cta * 32 + lane), hv);
                } else {
                    const uint32_t lo = enc(pack_bf(r.x, r.y)), hi = enc(pack_bf(r.z, r.w));
                    pub32(it, scr32 + (G_Q * 4 + cta * 64 + lane), lo);
                    pub32(it, scr32 + (G_Q * 4 + cta * 64 + 32 + lane), hi);
                    if (it == 0) { mod_lo = lo; mod_hi = hi; }
                }
            }
        }
        if (tid == 192) mbar_arrive(bars + (RELW + it) * 8);
    }

    {
        constexpr int PER = (G_TOTAL - G_STAT + 71) / 72;
        static_assert(PER <= 1024, "clear split");
        const int i = G_STAT + max(cta - 36, 0) * PER + tid, end = cta < 36 ? 0 : min(i - tid + PER, G_TOTAL);
#pragma unroll
        for (int k = 0; k < 1024; k += 256) clr128(i + k < end, scr + i + k);
#pragma unroll
        for (int k = 0; k < 1024; k += 256) cleared |= back32(i + k < end, scr + i + k);
    }
    if (tid < 128) {
        uint4 v[1];
        poll<1, SLP>(v, scr + (G_Q + g * 128 + tid), 0);
        put_piece(v[0], sm + SM_AVA + tid * 4);
    }
    if (cleared) __trap();
    cbar();
    if (warp == 7) {
        uint32_t* dst = scr32 + (G_MOD * 4 + ((cta / 72) * 1152 + (cta % 36) * 16) * 2 + lane);
        pub32(cta >= 36 && cta < 108, dst, mod_lo);
        pub32(cta >= 36 && cta < 108, dst + 1152, mod_hi);
    }
    STAMP0(5);
    {
        auto fetch_mod = [&]() {
            if (warp < 5) {
            const int t = min(tid, 143);
            uint4 v[4];
            poll<4, SLP>(v, scr + (G_MOD + 288 + t), 144);
#pragma unroll
            for (int i = 0; i < 4; i++) {
                uint4 u = unzip(v[i]);
                if (i >= 2) {
                    u.x = pack_bf(1.0f + bf_lo(u.x), 1.0f + bf_hi(u.x)); u.y = pack_bf(1.0f + bf_lo(u.y), 1.0f + bf_hi(u.y));
                    u.z = pack_bf(1.0f + bf_lo(u.z), 1.0f + bf_hi(u.z)); u.w = pack_bf(1.0f + bf_lo(u.w), 1.0f + bf_hi(u.w));
                }
                const uint32_t d = sm + (i >= 2 ? SM_CB1 : SM_SB) + (t + 144 * (i & 1)) * 4;
                sts32(d, u.x); sts32(d + AV_PITCH, u.y); sts32(d + 2 * AV_PITCH, u.z); sts32(d + 3 * AV_PITCH, u.w);
            }
        } else if (warp == 7 && cta < 72) {
            sts16(sm + SM_XR + (lane & 7) * 8 + (lane >> 3) * 2,
                  reinterpret_cast<const unsigned short*>(x)[(lane >> 3) * D_MODEL + cta * 8 + (lane & 7)]);
            uint4 v[2];
            poll<2, SLP>(v, scr + (G_MOD + cta * 4 + ((lane & 7) >> 1)), 864);
            sts128(sm + SM_QS + (lane & 7) * 16, make_uint4(~((lane & 1) ? v[0].z : v[0].x), ~((lane & 1) ? v[0].w : v[0].y),
                                                            ~((lane & 1) ? v[1].z : v[1].x), ~((lane & 1) ? v[1].w : v[1].y)));
        }
        };
        const uint32_t koff = (hf * 32 + (mi & 1) * 8 + r8) * 128;
        uint32_t sw[4];
#pragma unroll
        for (int c = 0; c < 4; c++) sw[c] = koff + (((2 * c + (mi >> 1)) ^ r8) << 4);
#pragma unroll 1
        for (int i = pr; i < TILES; i += 4) {
            uint32_t qf[8][2];
#pragma unroll
            for (int ks = 0; ks < 8; ks++) {
                const uint32_t a = sm + SM_AVA + (i >> 3) * AV_PITCH + ((lane >> 2) & 1) * 256 + ks * 32 + (lane & 3) * 4;
                qf[ks][0] = lds32(a); qf[ks][1] = lds32(a + 16);
            }
            mbar_wait(bars + (CH_KV + i) * 8);
            const uint32_t tb = sm + (i % NSLOT) * TILE_BYTES;
            float c[4][4];
#pragma unroll
            for (int u = 0; u < 4; u++) { c[u][0] = c[u][1] = c[u][2] = c[u][3] = 0.f; }
#pragma unroll
            for (int ks = 0; ks < 4; ks++) {
#pragma unroll
                for (int u = 0; u < 4; u++) {
                    uint32_t a[4];
                    ldsm4(a, tb + (u >> 1) * 8192 + (u & 1) * 2048 + sw[ks]);
                    mma16816(c[u], a, qf[(u >> 1) * 4 + ks][0], qf[(u >> 1) * 4 + ks][1]);
                }
            }
            __syncwarp();
            if (lane == 0) mbar_arrive(bars + (REL + i) * 8);
            const bool t1 = (lane & 2) != 0, hi = (lane & 1) != 0;
            const float p0 = t1 ? (hi ? c[1][2] + c[3][2] : c[1][0] + c[3][0]) : (hi ? c[0][2] + c[2][2] : c[0][0] + c[2][0]);
            const float p1 = t1 ? (hi ? c[1][3] + c[3][3] : c[1][1] + c[3][1]) : (hi ? c[0][3] + c[2][3] : c[0][1] + c[2][1]);
            const uint32_t w = pack_bf(bfr(p0) * 0.08838834764831845f, bfr(p1) * 0.08838834764831845f);
            const uint32_t a = sm + SM_SC + (i * 64 + hf * 32 + (lane & 3) * 8 + (lane >> 2)) * 2;
            sts16(a, w & 0xFFFFu);
            sts16(a + 4096, w >> 16);
            if ((i >> 2) == MODAT) fetch_mod();
        }
    }
    cbar();
    STAMP0(6);

    {
        const uint32_t a = sm + SM_SC + tid * 32;
        const uint4 u0 = lds128(a), u1 = lds128(a + 16);
        const uint32_t w[8] = {u0.x, u0.y, u0.z, u0.w, u1.x, u1.y, u1.z, u1.w};
        float e[16], m = -INFINITY;
#pragma unroll
        for (int i = 0; i < 8; i++) { e[2 * i] = bf_lo(w[i]); e[2 * i + 1] = bf_hi(w[i]); m = fmaxf(m, fmaxf(e[2 * i], e[2 * i + 1])); }
#pragma unroll
        for (int o = 16; o; o >>= 1) m = fmaxf(m, __shfl_xor_sync(0xffffffffu, m, o));
        float l = 0.f;
#pragma unroll
        for (int i = 0; i < 16; i++) { e[i] = ex2((e[i] - m) * LOG2E); l += e[i]; }
#pragma unroll
        for (int o = 16; o; o >>= 1) l += __shfl_xor_sync(0xffffffffu, l, o);
        if (lane == 0) sts64(sm + SM_RED + warp * 8, encf(m), encf(l));
        cbar();
        if (warp == 0) {
            pub32(lane < 16, scr32 + (G_STAT * 4 + cta * 32 + lane), lds32(sm + SM_RED + (lane & 15) * 4));
            uint4 v[1];
            poll<1, SLP>(v, scr + (G_STAT + (g * 8 + (lane >> 2)) * 8 + (lane & 3)), 0);
            const float ma = decf(v[0].x), mb = decf(v[0].z);
            float ga = ma, gb = mb;
#pragma unroll
            for (int o = 4; o < 32; o <<= 1) { ga = fmaxf(ga, __shfl_xor_sync(0xffffffffu, ga, o)); gb = fmaxf(gb, __shfl_xor_sync(0xffffffffu, gb, o)); }
            float la = decf(v[0].y) * ex2((ma - ga) * LOG2E), lb = decf(v[0].w) * ex2((mb - gb) * LOG2E);
#pragma unroll
            for (int o = 4; o < 32; o <<= 1) { la += __shfl_xor_sync(0xffffffffu, la, o); lb += __shfl_xor_sync(0xffffffffu, lb, o); }
            sts128f(sm + SM_RED + 64 + (lane & 3) * 16, ga, rcp(la), gb, rcp(lb));
        }
        cbar();
        const float f = ex2((m - ldsf(sm + SM_RED + 64 + warp * 8)) * LOG2E) * ldsf(sm + SM_RED + 68 + warp * 8);
        uint4 o0, o1;
        o0.x = pack_bf(e[0] * f, e[1] * f); o0.y = pack_bf(e[2] * f, e[3] * f); o0.z = pack_bf(e[4] * f, e[5] * f); o0.w = pack_bf(e[6] * f, e[7] * f);
        o1.x = pack_bf(e[8] * f, e[9] * f); o1.y = pack_bf(e[10] * f, e[11] * f); o1.z = pack_bf(e[12] * f, e[13] * f); o1.w = pack_bf(e[14] * f, e[15] * f);
        sts128(a, o0); sts128(a + 16, o1);
        cbar();
    }
    STAMP0(7);

    uint32_t wa[2][18][4];
    const bool pw = warp < 4 || (warp == 4 && j < 4);
    const uint32_t astep = warp < 4 ? 2048 : 512;
    const uint32_t aoff = warp < 4 ? ((mi >> 1) * 8 + r8) * 128 + (((warp * 2 + (mi & 1)) ^ r8) << 4)
                                   : ((mi >> 1) * 8 + r8) * 32 + (((mi & 1) ^ (r8 >> 2)) << 4);
    const uint32_t abase[2] = {sm + (warp < 4 ? SM_WO : SM_X) + aoff, sm + (warp < 4 ? SM_WD : SM_X + 8192) + aoff};
    int nl = 0;
    auto proj_bar = [&](int rd) {
        const int c = min(lane, 3 + 2 * rd);
        return bars + (warp < 4 ? (rd ? CH_WD : CH_WO) + c : (rd ? CH_GB : CH_WO) + 4 + c / (2 + rd)) * 8;
    };
    auto proj_load = [&](int rd, int c) {
#pragma unroll
        for (int u = c * (4 - rd); u < (c + 1) * (4 - rd); u++) ldsm4t(wa[rd][u], abase[rd] + u * astep);
        nl = c + 1;
    };
    auto proj_more = [&](int rd, bool t) {
        const uint32_t lb = __ballot_sync(0xffffffffu, t);
#pragma unroll
        for (int c = 0; c < 4 + 2 * rd; c++) if (nl == c && ((lb >> c) & 1)) proj_load(rd, c);
    };
    {
        float o[4][4];
#pragma unroll
        for (int u = 0; u < 4; u++) { o[u][0] = o[u][1] = o[u][2] = o[u][3] = 0.f; }
        const uint32_t voff = hf * 8192 + ((mi >> 1) * 8 + r8) * 128;
        uint32_t sw[4];
#pragma unroll
        for (int u = 0; u < 4; u++) sw[u] = voff + (((2 * u + (mi & 1)) ^ r8) << 4);
        const uint32_t pb = sm + SM_SC + ((lane >> 2) & 1) * 4096 + (lane & 3) * 4 - TILES * 128;
        auto v_tile = [&](int i) {
            uint32_t pf[4][2];
#pragma unroll
            for (int kk = 0; kk < 4; kk++) { pf[kk][0] = lds32(pb + i * 128 + kk * 32); pf[kk][1] = lds32(pb + i * 128 + kk * 32 + 16); }
            const uint32_t tb = sm + slot_of(i) * TILE_BYTES;
            mbar_wait(bars + (CH_KV + i) * 8);
#pragma unroll
            for (int kk = 0; kk < 4; kk++) {
#pragma unroll
                for (int u = 0; u < 4; u++) {
                    uint32_t a[4];
                    ldsm4t(a, tb + kk * 2048 + sw[u]);
                    mma16816(o[u], a, pf[kk][0], pf[kk][1]);
                }
            }
            __syncwarp();
            if (lane == 0) mbar_arrive(bars + (REL + i) * 8);
        };
#pragma unroll 1
        for (int t = 0; t <= 8; t++) {
            const int gb = t == 8 ? 3 : (t & 1) ? (t - 3) >> 1 : -1;
            bool todo = t < 8;
            uint4 v[2];
            poll<2, SLP_O, false>(v, scr + (G_OPART + (gb * NCTA + g * 8 + (lane & 3) * 2) * 64 + (tid >> 2)), 64, gb < 0 ? 3 : 0, [&] {
                if (todo) {
                v_tile(TILES + pr + 4 * t);
            if (t & 1) {
                const int u = lane & 3;
                const uint32_t red = sm + ((t & 2) ? SM_RED : SM_AVB);
                const uint32_t a = red + pr * 1024 + (hf * 64 + u * 16 + (lane >> 2)) * 4;
                float w[4];
#pragma unroll
                for (int q = 0; q < 4; q++) w[q] = u == 0 ? o[0][q] : u == 1 ? o[1][q] : u == 2 ? o[2][q] : o[3][q];
                stsf(a, w[0]); stsf(a + 512, w[1]); stsf(a + 32, w[2]); stsf(a + 512 + 32, w[3]);
#pragma unroll
                for (int q = 0; q < 4; q++) { o[q][0] = o[q][1] = o[q][2] = o[q][3] = 0.f; }
                cbar();
                const uint32_t r = red + tid * 4;
                pub32(true, scr32 + (G_OPART * 4 + ((t >> 1) * NCTA + cta) * 256 + tid),
                      encf((ldsf(r) + ldsf(r + 1024)) + (ldsf(r + 2048) + ldsf(r + 3072))));
                STAMPT(0, 8);
            }
                } else if (warp < 5 && nl < 4) proj_more(0, mbar_test(proj_bar(0)));
                todo = false;
            });
            if (gb >= 0) {
                const bool od = lane & 1;
                const float s0 = decf(v[0].x) + decf(v[1].x), s1 = decf(v[0].y) + decf(v[1].y);
                const float s2 = decf(v[0].z) + decf(v[1].z), s3 = decf(v[0].w) + decf(v[1].w);
                float a0 = (od ? s2 : s0) + __shfl_xor_sync(0xffffffffu, od ? s0 : s2, 1);
                float a1 = (od ? s3 : s1) + __shfl_xor_sync(0xffffffffu, od ? s1 : s3, 1);
                a0 += __shfl_xor_sync(0xffffffffu, a0, 2);
                a1 += __shfl_xor_sync(0xffffffffu, a1, 2);
                sts32(sm + SM_AVA + gb * AV_PITCH + (tid >> 2) * 8 + (lane & 1) * 4, pack_bf(a0, a1));
            }
        }
    }

    auto project = [&](int rd) {
        uint32_t b4[9][4];
#pragma unroll
        for (int u = 0; u < 8 + rd; u++) ldsm4(b4[u], sm + SM_AVA + (r8 & 3) * AV_PITCH + mi * 16 + u * 64);
        if (__builtin_expect(nl < 4 + 2 * rd, 0)) {
#pragma unroll 1
            for (unsigned it = 0; nl < 4 + 2 * rd; it++) {
                proj_more(rd, mbar_test(proj_bar(rd)));
                if (it > 16 * SPIN_LIMIT) __trap();
            }
        }
        float c[4][4];
#pragma unroll
        for (int u = 0; u < 4; u++) { c[u][0] = c[u][1] = c[u][2] = c[u][3] = 0.f; }
#pragma unroll
        for (int u = 0; u < 16 + 2 * rd; u++) mma16816(c[u & 3], wa[rd][u], b4[u >> 1][(u & 1) * 2], b4[u >> 1][(u & 1) * 2 + 1]);
        const bool hi = (lane & 2) != 0;
        const int ob = (warp < 4 ? j * 8 + warp * 2 : 64 + j * 2) + (hi ? 1 : 0);
        pub64(pw, scr64 + ((G_PART + rd * 72 * 128 + (ob * 16 + g) * 8) * 2 + (lane >> 2) * 2 + (lane & 1)),
              encf(hi ? (c[2][2] + c[3][2]) + (c[0][2] + c[1][2]) : (c[2][0] + c[3][0]) + (c[0][0] + c[1][0])),
              encf(hi ? (c[2][3] + c[3][3]) + (c[0][3] + c[1][3]) : (c[2][1] + c[3][1]) + (c[0][1] + c[1][1])));
        STAMPT(0, 10 + 5 * rd);
    };
    auto reduce = [&](int rd) {
        const uint32_t g01 = lds32(sm + SM_QS + (lane & 7) * 16 + rd * 8), g23 = lds32(sm + SM_QS + (lane & 7) * 16 + rd * 8 + 4);
        const uint32_t r01 = lds32(sm + SM_XR + (lane & 7) * 8), r23 = lds32(sm + SM_XR + 4 + (lane & 7) * 8);
        uint4 w[4];
        poll<4, SLP_R>(w, scr + (G_PART + rd * 72 * 128 + cta * 128 + lane), 32);
        float t[4] = {(decf(w[0].x) + decf(w[1].x)) + (decf(w[2].x) + decf(w[3].x)), (decf(w[0].y) + decf(w[1].y)) + (decf(w[2].y) + decf(w[3].y)),
                      (decf(w[0].z) + decf(w[1].z)) + (decf(w[2].z) + decf(w[3].z)), (decf(w[0].w) + decf(w[1].w)) + (decf(w[2].w) + decf(w[3].w))};
#pragma unroll
        for (int q = 0; q < 4; q++) t[q] += __shfl_xor_sync(0xffffffffu, t[q], 8);
#pragma unroll
        for (int q = 0; q < 4; q++) t[q] += __shfl_xor_sync(0xffffffffu, t[q], 16);
        const uint32_t x01 = add2(r01, mul2(g01, pack_bf(t[0], t[1]))), x23 = add2(r23, mul2(g23, pack_bf(t[2], t[3])));
        if (rd == 1) {
            const uint32_t ov = (lane & 16) ? x23 : x01;
            st16(true, out + ((lane >> 3) * D_MODEL + cta * 8 + (lane & 7)), (lane & 8) ? ov >> 16 : ov);
        } else {
#pragma unroll
            for (int i = 0; i < (NREP + 3) / 4; i++)
                pub64(i * 4 + (lane >> 3) < NREP, scr64 + (G_X1 * 2 + (i * 4 + (lane >> 3)) * 576 + cta * 8 + (lane & 7)), enc(x01), enc(x23));
            sts64(sm + SM_XR + (lane & 7) * 8, x01, x23);
        }
        STAMPT(224, 18 + rd);
    };
    STAMPT(0, 34);
    if (__builtin_expect(warp < 5, 1)) {
        cbar();
        STAMP0(9);
        project(0);
    } else {
        asm volatile("bar.arrive 1, 256;" ::: "memory");
        if (warp == 7 && cta < 72) reduce(0);
    }
    {
        uint32_t wg[5][5][4];
        const bool four = warp >= 4;
        uint32_t gbar;
        {
            const int ks = min(warp + 8 * (lane >> 1), 35), t = ks / 3;
            gbar = bars + ((xg && (lane & 1)) ? (ks < 24 ? CH_GA + 8 + (ks / 12) * 2 : CH_GB + 4) : t < 8 ? CH_GA + t : CH_GB + t - 8) * 8;
        }
        auto gu_load = [&](int i) {
            const int ks = warp + 8 * i, k = ks * 16 + (mi >> 1) * 8 + r8;
            const uint32_t ag = sm + (ks < 30 ? SM_WG : -61440) + k * 128;
#pragma unroll
            for (int u = 0; u < 4; u++) ldsm4t(wg[i][u], ag + (((2 * u + (mi & 1)) ^ r8) << 4));
            if (xg) ldsm4t(wg[i][4], sm + SM_X + k * 32 + (((mi & 1) ^ (r8 >> 2)) << 4));
            nl = i + 1;
        };
        auto gu_more = [&](bool t, int n) {
            const uint32_t lb = __ballot_sync(0xffffffffu, t);
#pragma unroll
            for (int i = 0; i < n; i++) if (nl == i && ((lb >> (2 * i)) & 3) == 3 && (i < 4 || !four)) gu_load(i);
        };
        nl = 0;
        gather576<SLP_X, GATE_X>(scr + (G_X1 + (g % NREP) * 288), sm + SM_AVB, warp, lane, [&] { if (nl < (four ? 4 : 5)) gu_more(mbar_test(gbar), 5); });
        STAMPT(0, 39);
        cbar();
        STAMP0(11);
        uint32_t bq[5][2];
        {
            const uint32_t fo = bfrag + warp * 32;
            const bool gt = mbar_test(gbar);
#pragma unroll
            for (int i = 0; i < 5; i++) { bq[i][0] = lds32(sm + SM_AVB + fo + i * 256); bq[i][1] = lds32(sm + SM_AVB + fo + i * 256 + 16); }
            const uint32_t piv2 = lane < 16 ? 0u : __byte_perm(lds32(sm + SM_AVB + ((lane >> 2) & 3) * AV_PITCH), 0, 0x1010);
            float m0[4] = {0.f, 0.f, 0.f, 0.f}, m1[4] = {0.f, 0.f, 0.f, 0.f};
#pragma unroll
            for (int i = 0; i < 5; i++) {
                uint32_t d[4] = {sub2(bq[i][0], piv2), 0x3F803F80u, sub2(bq[i][1], piv2), 0x3F803F80u};
                if (i == 4 && four) d[0] = d[2] = 0;
                mma16816((i & 1) ? m1 : m0, d, d[0], d[2]);
            }
            if ((lane & 3) == (lane >> 3))
                sts64(sm + SM_RED + (lane >> 2) * 80 + warp * 8, __float_as_uint((lane & 4) ? m0[3] + m1[3] : m0[2] + m1[2]),
                      __float_as_uint((lane & 4) ? m0[1] + m1[1] : m0[0] + m1[0]));
            if (nl < (four ? 4 : 5)) gu_more(gt, 5);
            cbar();
            const uint32_t ra = sm + SM_RED + (lane >> 2) * 80;
            const float4 p0 = lds128f(ra), p1 = lds128f(ra + 16), p2 = lds128f(ra + 32), p3 = lds128f(ra + 48);
            const float sd = (((p0.x + p0.z) + (p1.x + p1.z)) + ((p2.x + p2.z) + (p3.x + p3.z))) * (1.0f / D_MODEL);
            const float sq = ((p0.y + p0.w) + (p1.y + p1.w)) + ((p2.y + p2.w) + (p3.y + p3.w));
            float mean = bf_hi(piv2) + sd, var = fmaf(sq, 1.0f / D_MODEL, -sd * sd);
            const float mean_o = __shfl_xor_sync(0xffffffffu, mean, 16), var_o = __shfl_xor_sync(0xffffffffu, var, 16);
            uint32_t c1[5][2], sb[5][2];
#pragma unroll
            for (int i = 0; i < 5; i++) {
                c1[i][0] = lds32(sm + SM_CB1 + fo + i * 256); c1[i][1] = lds32(sm + SM_CB1 + fo + i * 256 + 16);
                sb[i][0] = lds32(sm + SM_SB + fo + i * 256); sb[i][1] = lds32(sm + SM_SB + fo + i * 256 + 16);
            }
            const float mean_r = lane < 16 ? mean : mean_o, var_r = lane < 16 ? var : var_o;
            if ((mean_r * mean_r > 16.0f * var_r) == (lane < 16)) { mean = mean_o; var = var_o; }
            const float mean_b = bfr(mean), rden = ln_rden(var);
            STAMPT(0, 40);
            const uint32_t mean2 = __byte_perm(__float_as_uint(mean_b), 0, 0x3232);
#pragma unroll
            for (int i = 0; i < 5; i++) {
                bq[i][0] = ln_mod2(bq[i][0], mean2, rden, c1[i][0], sb[i][0]);
                bq[i][1] = ln_mod2(bq[i][1], mean2, rden, c1[i][1], sb[i][1]);
            }
        }
        STAMPT(0, 12);
        {
            float c[5][4];
#pragma unroll
            for (int u = 0; u < 5; u++) { c[u][0] = c[u][1] = c[u][2] = c[u][3] = 0.f; }
            const int nw = four ? 4 : 5;
            if (__builtin_expect(nl < nw, 0)) {
#pragma unroll 1
                for (unsigned it = 0; nl < nw; it++) {
                    gu_more(mbar_test(gbar), 5);
                    if (it > 16 * SPIN_LIMIT) __trap();
                }
            }
#pragma unroll
            for (int i = 0; i < 5; i++) {
                if (i < 4 || !four) {
#pragma unroll
                    for (int u = 0; u < 4; u++) mma16816(c[u], wg[i][u], bq[i][0], bq[i][1]);
                    if (xg) mma16816(c[4], wg[i][4], bq[i][0], bq[i][1]);
                }
            }
            STAMPT(0, 43);
            const bool t1 = (lane & 2) != 0;
            const uint32_t rb = sm + SM_GRED + warp * 1280 + ((lane >> 2) * 2 + (lane & 1)) * 16;
#pragma unroll
            for (int u = 0; u < 4; u += 2)
                sts128f(rb + (t1 ? 256 : 0) + u * 256, t1 ? c[u + 1][0] : c[u][0], t1 ? c[u + 1][1] : c[u][1], t1 ? c[u + 1][2] : c[u][2], t1 ? c[u + 1][3] : c[u][3]);
            sts128f(rb + 1024, c[4][0], c[4][1], c[4][2], c[4][3]);
        }
        STAMPT(0, 44);
        if (__builtin_expect(warp >= 5, 1)) {
            cbar();
            const int t = tid - 160;
            float4 r = sum8(sm + SM_GRED + min(t, 79) * 16, 1280);
            if ((g & 1) == 0) { r.x = gelu(bfr(r.x)); r.y = gelu(bfr(r.y)); r.z = gelu(bfr(r.z)); r.w = gelu(bfr(r.w)); }
            uint32_t* dst = scr32 + (G_ACT * 4 + (g & 1) * 9216 + (t < 64 ? f0 * 2 + (t >> 4) * 32 : fx * 2) + (t & 15));
            pub32(t < (xg ? 80 : 64), dst, enc(pack_bf(r.x, r.y)));
            pub32(t < (xg ? 80 : 64), dst + 16, enc(pack_bf(r.z, r.w)));
            STAMPT(160, 13);
            static_assert(G_Q - G_H <= NCTA * 32, "clear split");
            clr128(t < 32 && G_H + cta * 32 + t < G_Q, scr + (G_H + cta * 32 + t));
            if (warp == 7 && cta < 72) reduce(1);
        } else {
            asm volatile("bar.arrive 1, 256;" ::: "memory");
            nl = 0;
            uint4 v[2];
            const int t = min(tid, 143);
            poll<2, SLP_A, false>(v, scr + (G_ACT + g * 144 + t), 2304, 0,
                                  [&] { if (nl < 6) proj_more(1, mbar_test(proj_bar(1))); });
            put_piece(make_uint4(~mul2(~v[0].x, ~v[1].x), ~mul2(~v[0].y, ~v[1].y), ~mul2(~v[0].z, ~v[1].z), ~mul2(~v[0].w, ~v[1].w)),
                      sm + SM_AVA + t * 4);
            STAMPT(0, 35);
            asm volatile("bar.sync 3, 160;" ::: "memory");
            STAMP0(14);
            project(1);
        }
    }
    }
}

typedef CUresult (*EncodeFn)(CUtensorMap*, CUtensorMapDataType, cuuint32_t, void*, const cuuint64_t*, const cuuint64_t*,
                             const cuuint32_t*, const cuuint32_t*, CUtensorMapInterleave, CUtensorMapSwizzle,
                             CUtensorMapL2promotion, CUtensorMapFloatOOBfill);

void make3d(EncodeFn fn, CUtensorMap* m, const void* p, uint64_t d0, uint64_t d1, uint64_t d2, uint64_t s1, uint64_t s2,
            uint32_t b0, uint32_t b1, uint32_t b2, CUtensorMapSwizzle sw, CUtensorMapL2promotion promo) {
    cuuint64_t gd[3] = {d0, d1, d2};
    cuuint64_t gs[2] = {s1, s2};
    cuuint32_t bx[3] = {b0, b1, b2};
    cuuint32_t es[3] = {1, 1, 1};
    fn(m, CU_TENSOR_MAP_DATA_TYPE_BFLOAT16, 3, const_cast<void*>(p), gd, gs, bx, es, CU_TENSOR_MAP_INTERLEAVE_NONE, sw, promo,
       CU_TENSOR_MAP_FLOAT_OOB_FILL_NONE);
}

}

extern "C" void kernel_launch(void* const* d_in, const int* in_sizes, int n_in, void* d_out, int out_size) {
    (void)in_sizes; (void)n_in; (void)out_size;
    EncodeFn fn = nullptr;
    cudaDriverEntryPointQueryResult qr;
    cudaGetDriverEntryPoint("cuTensorMapEncodeTiled", (void**)&fn, cudaEnableDefault, &qr);
    cudaFuncSetAttribute(fused_block_kernel, cudaFuncAttributeMaxDynamicSharedMemorySize, SM_LAUNCH);
    Params prm;
#define WPROMO CU_TENSOR_MAP_L2_PROMOTION_L2_128B
    const CUtensorMapL2promotion P128 = WPROMO, P256 = KVPROMO;
    make3d(fn, &prm.m[M_K], d_in[1], 64, (uint64_t)NB * 16 * SK, 2, 256, 128, 64, 64, 2, CU_TENSOR_MAP_SWIZZLE_128B, P256);
    make3d(fn, &prm.m[M_V], d_in[2], 64, (uint64_t)NB * 16 * SK, 2, 256, 128, 64, 64, 2, CU_TENSOR_MAP_SWIZZLE_128B, P256);
    make3d(fn, &prm.m[M_WMOD], d_in[10], D_MODEL, D_MODEL, 6, 6 * D_MODEL * 2, D_MODEL * 2, 16, 192, 2, CU_TENSOR_MAP_SWIZZLE_32B, P128);
    make3d(fn, &prm.m[M_WQ], d_in[3], 4096, D_MODEL, 1, 8192, 8192 * D_MODEL, 32, 192, 1, CU_TENSOR_MAP_SWIZZLE_64B, P128);
    for (int x = 0; x < 2; x++) {
        const CUtensorMapSwizzle sp = x ? CU_TENSOR_MAP_SWIZZLE_32B : CU_TENSOR_MAP_SWIZZLE_128B;
        make3d(fn, &prm.m[M_WO + 4 * x], d_in[4], D_MODEL, 4096, 1, D_MODEL * 2, D_MODEL * 2 * 4096, x ? 16 : 64, x ? 128 : 64, 1, sp, P128);
        make3d(fn, &prm.m[M_WD + 4 * x], d_in[8], D_MODEL, FF, 1, D_MODEL * 2, D_MODEL * 2 * FF, x ? 16 : 64, x ? 144 : 48, 1, sp, P128);
        make3d(fn, &prm.m[M_WG + 4 * x], d_in[6], FF, D_MODEL, 1, FF * 2, FF * 2 * D_MODEL, x ? 16 : 64, x ? 192 : 48, 1, sp, P128);
        make3d(fn, &prm.m[M_WU + 4 * x], d_in[7], FF, D_MODEL, 1, FF * 2, FF * 2 * D_MODEL, x ? 16 : 64, x ? 192 : 48, 1, sp, P128);
    }
    void* scr = nullptr;
    void* plan = nullptr;
    cudaGetSymbolAddress(&scr, g_scr);
    cudaGetSymbolAddress(&plan, g_plan);
    fused_block_kernel<<<NCTA, NTHREADS, SM_LAUNCH>>>(prm, (const __nv_bfloat16*)d_in[0], (const __nv_bfloat16*)d_in[9],
                                                     (__nv_bfloat16*)d_out, (uint4*)scr, plan);
}
```

```cpp
#include <cuda_runtime.h>
#include <cuda_bf16.h>
#include <cuda.h>
#include <stdint.h>

namespace {

constexpr int D_MODEL = 576;
constexpr int NB = 4;
constexpr int SK = 4096;
constexpr int FF = 4608;
constexpr int NCTA = 128;
constexpr int NTHREADS = 320;
constexpr int NSLOT = 12;
constexpr int TILE_BYTES = 16384;
constexpr int TILES = 32;
constexpr int AV_PITCH = 1168;

constexpr int SM_W0 = 7 * TILE_BYTES;
constexpr int SM_X = 4 * TILE_BYTES;
constexpr int SM_WO = SM_X + 18432;
constexpr int SM_WG = SM_WO + 32768;
constexpr int SM_WD = 0;
constexpr int SM_GRED = 3 * TILE_BYTES;
constexpr int SM_SC = NSLOT * TILE_BYTES;
constexpr int SM_RED = SM_SC + 8192;
constexpr int SM_AVA = SM_RED + 4096;
constexpr int SM_AVB = SM_AVA + 4 * AV_PITCH;
constexpr int SM_CB1 = SM_AVB + 4 * AV_PITCH;
constexpr int SM_SB = SM_CB1 + 4 * AV_PITCH;
constexpr int SM_QS = SM_SB + 4 * AV_PITCH;
constexpr int SM_XR = SM_QS + 128;
constexpr int SM_BAR = SM_XR + 64;
constexpr int CH_KV = 6, CH_WO = 70, CH_GU = 74, CH_WD = 86, CH_X = 92, NCHUNK = 98;
constexpr int REL = NCHUNK, RELW = REL + 64, NBAR = RELW + 2;
constexpr int SM_TAB = SM_BAR + 1312;
static_assert(NBAR * 8 <= 1312, "bars");
constexpr int SM_ADJ = SM_TAB + NCHUNK * 16;
constexpr int SM_ORG = SM_ADJ + 16;
constexpr int SM_TOTAL = SM_ORG + 96;
static_assert(SM_TOTAL <= 232448, "smem");
constexpr int NHARD = 4;

constexpr unsigned SPIN_LIMIT = 1u << 22;
constexpr float LOG2E = 1.4426950408889634f;

enum { M_K = 0, M_V, M_WMOD, M_WQ, M_WO, M_WD, M_WG, M_WU, M_WOX, M_WDX, M_WGX, M_WUX, NMAPS };
struct alignas(16) Plan { uint32_t e[NCHUNK][4]; };
struct Params { CUtensorMap m[NMAPS]; };

constexpr Plan make_plan() {
    Plan pl = {};
    const int paced_from = 13, win_start = 48, win_main = 64;
    const int win_wo = 44, win_gu = 48, win_wd = 32;
    const int slack_main = 32, lag_main = 56, slack_tail = 6, lag_tail = 16;
    const int xkb = 3;
    const unsigned char tail[28] = {70, 92, 71, 93, 72, 73, 74, 75, 94, 76, 77, 78, 79, 95, 80, 81, 82, 83, 96, 97, 84, 85,
                                    86, 87, 88, 89, 90, 91};
    int order[NCHUNK] = {}, kb[NCHUNK] = {}, last_user[NSLOT] = {}, cum = 0;
    for (int p = 0; p < NCHUNK; p++) order[p] = p < 3 ? p : p == 3 ? CH_KV : p <= CH_KV ? p - 1 : p < CH_WO ? p : tail[p - CH_WO];
    for (int i = 0; i < NSLOT; i++) last_user[i] = i >= 9 ? RELW + 1 : i >= 7 ? RELW : 0;
    for (int p = 0; p < NCHUNK; p++) {
        const int c = order[p];
        int map = 0, dst = 0, row = 0, bytes = 0;
        if (c < CH_KV) { map = c < 3 ? M_WMOD : M_WQ; dst = SM_W0 + c * 12288; bytes = 12288; row = (c % 3) * 192; }
        else if (c < CH_WO) { const int i = c - CH_KV; map = i / TILES; dst = (i % NSLOT) * TILE_BYTES; bytes = TILE_BYTES; row = i % TILES; }
        else if (c < CH_GU) { const int t = c - CH_WO; map = M_WO; dst = SM_WO + t * 8192; bytes = 8192; row = t * 64; }
        else if (c < CH_WD) { const int t = c - CH_GU; map = M_WG; dst = SM_WG + t * 6144; bytes = 6144; row = t * 48; }
        else if (c < CH_X) { const int t = c - CH_WD; map = M_WD; dst = SM_WD + t * 6144; bytes = 6144; row = t * 48; }
        else { dst = SM_X; row = c - CH_X; }
        kb[p] = bytes ? bytes / 1024 : xkb;
        cum += kb[p];
        unsigned bar4 = 0;
        if (c >= CH_KV) bar4 = last_user[dst / TILE_BYTES] | (last_user[(dst + (bytes ? bytes : 18432) - 1) / TILE_BYTES] << 8);
        if (c >= CH_KV && c < CH_WO) last_user[dst / TILE_BYTES] = REL + c - CH_KV;
        const bool tl = p >= CH_WO;
        const int win = p < paced_from ? win_start : !tl ? win_main : p < CH_WO + 6 ? win_wo : p < CH_WO + 22 ? win_gu : win_wd;
        const int slack = p < paced_from ? 0 : tl ? slack_tail : slack_main;
        for (int k = 0; k < 2; k++) {
            const int lim = k ? win - slack : win + slack;
            int q = p - 1, sum = kb[p];
            while (q > 0 && (sum + kb[q] <= lim || order[q] >= CH_X)) sum += kb[q--];
            bar4 |= (unsigned)order[q < 0 ? 0 : q] << (16 + 8 * k);
        }
        const int thr = cum - win - (tl ? lag_tail : lag_main);
        pl.e[p][0] = dst | (map << 20) | (c << 24);
        pl.e[p][1] = row | (bytes << 16);
        pl.e[p][2] = (unsigned)(thr < 0 ? 0 : thr) | ((unsigned)cum << 18);
        pl.e[p][3] = bar4;
    }
    return pl;
}
__device__ const Plan g_plan = make_plan();

constexpr int NREP = 4;
constexpr int G_CNT = 0;
constexpr int G_H = G_CNT + 8;
constexpr int G_MOD = G_H + NREP * 288;
constexpr int G_Q = G_MOD + 1152;
constexpr int G_STAT = G_Q + 2048;
constexpr int G_OPART = G_STAT + NCTA * 8;
constexpr int G_X1 = G_OPART + 4 * NCTA * 64;
constexpr int G_ACT = G_X1 + NREP * 288;
constexpr int G_PART = G_ACT + 2 * 2304;
constexpr int G_TOTAL = G_PART + 2 * 72 * 128;
__device__ __align__(128) uint4 g_scr[G_TOTAL];

__device__ __forceinline__ uint32_t enc(uint32_t w) { return max(~w, 1u); }
__device__ __forceinline__ uint32_t encf(float f) { return enc(__float_as_uint(f)); }
__device__ __forceinline__ float decf(uint32_t w) { return __uint_as_float(~w); }
__device__ __forceinline__ float bf_lo(uint32_t w) { return __uint_as_float(w << 16); }
__device__ __forceinline__ float bf_hi(uint32_t w) { return __uint_as_float(w & 0xFFFF0000u); }
__device__ __forceinline__ uint32_t pack_bf(float lo, float hi) {
    uint32_t r;
    asm("cvt.rn.bf16x2.f32 %0, %1, %2;" : "=r"(r) : "f"(hi), "f"(lo));
    return r;
}
__device__ __forceinline__ float bfr(float x) { return __uint_as_float(pack_bf(0.f, x)); }
__device__ __forceinline__ uint32_t mul2(uint32_t a, uint32_t b) { uint32_t r; asm("mul.rn.bf16x2 %0, %1, %2;" : "=r"(r) : "r"(a), "r"(b)); return r; }
__device__ __forceinline__ uint32_t add2(uint32_t a, uint32_t b) { uint32_t r; asm("add.rn.bf16x2 %0, %1, %2;" : "=r"(r) : "r"(a), "r"(b)); return r; }
__device__ __forceinline__ uint32_t sub2(uint32_t a, uint32_t b) { uint32_t r; asm("sub.rn.bf16x2 %0, %1, %2;" : "=r"(r) : "r"(a), "r"(b)); return r; }
__device__ __forceinline__ float ex2(float x) { float r; asm("ex2.approx.ftz.f32 %0, %1;" : "=f"(r) : "f"(x)); return r; }
__device__ __forceinline__ float rcp(float x) { float r; asm("rcp.approx.ftz.f32 %0, %1;" : "=f"(r) : "f"(x)); return r; }
__device__ __forceinline__ float fsqrt(float x) { float r; asm("sqrt.approx.ftz.f32 %0, %1;" : "=f"(r) : "f"(x)); return r; }
__device__ __forceinline__ float sigm(float x) { return rcp(1.0f + ex2(-LOG2E * x)); }
__device__ __forceinline__ float gelu(float g) { return g * sigm(1.5957691216057308f * (g + 0.044715f * g * g * g)); }
__device__ __forceinline__ void mbar_init(uint32_t bar, uint32_t cnt) {
    asm volatile("mbarrier.init.shared::cta.b64 [%0], %1;" ::"r"(bar), "r"(cnt) : "memory");
}
__device__ __forceinline__ void mbar_expect(uint32_t bar, uint32_t bytes) {
    asm volatile("mbarrier.arrive.expect_tx.shared::cta.b64 _, [%0], %1;" ::"r"(bar), "r"(bytes) : "memory");
}
__device__ __forceinline__ void mbar_arrive(uint32_t bar) {
    asm volatile("mbarrier.arrive.shared::cta.b64 _, [%0];" ::"r"(bar) : "memory");
}
__device__ __forceinline__ void mbar_wait(uint32_t bar) {
    asm volatile("{\n.reg .pred p;\n.reg .u32 n;\nmov.u32 n, 0;\n"
                 "W_%=:\nmbarrier.try_wait.parity.shared::cta.b64 p, [%0], 0;\n@p bra D_%=;\n"
                 "add.u32 n, n, 1;\nsetp.lt.u32 p, n, %1;\n@p bra W_%=;\ntrap;\nD_%=:\n}"
                 ::"r"(bar), "n"(SPIN_LIMIT) : "memory");
}
__device__ __forceinline__ bool mbar_test(uint32_t bar) {
    uint32_t ok;
    asm volatile("{\n.reg .pred p;\nmbarrier.test_wait.parity.shared::cta.b64 p, [%1], 0;\nselp.u32 %0, 1, 0, p;\n}" : "=r"(ok) : "r"(bar) : "memory");
    return ok != 0;
}
__device__ __forceinline__ void tma3(uint32_t dst, const CUtensorMap* m, int c0, int c1, int c2, uint32_t bar, uint64_t pol) {
    asm volatile("cp.async.bulk.tensor.3d.shared::cluster.global.mbarrier::complete_tx::bytes.L2::cache_hint [%0], [%1, {%3, %4, %5}], [%2], %6;"
                 ::"r"(dst), "l"(m), "r"(bar), "r"(c0), "r"(c1), "r"(c2), "l"(pol) : "memory");
}
__device__ __forceinline__ void cbar() { asm volatile("bar.sync 1, 256;" ::: "memory"); }
template <int ID>
__device__ __forceinline__ void arrive_if(bool p) {
    asm volatile("{\n.reg .pred q;\nsetp.ne.u32 q, %0, 0;\n@q bar.arrive %1, 256;\n}" ::"r"((uint32_t)p), "n"(ID) : "memory");
}
template <int ID>
__device__ __forceinline__ void await() { asm volatile("bar.sync %0, 256;" ::"n"(ID) : "memory"); }
__device__ __forceinline__ void ldsm4(uint32_t (&r)[4], uint32_t a) {
    asm volatile("ldmatrix.sync.aligned.m8n8.x4.shared.b16 {%0,%1,%2,%3}, [%4];"
                 : "=r"(r[0]), "=r"(r[1]), "=r"(r[2]), "=r"(r[3]) : "r"(a) : "memory");
}
__device__ __forceinline__ void ldsm4t(uint32_t (&r)[4], uint32_t a) {
    asm volatile("ldmatrix.sync.aligned.m8n8.x4.trans.shared.b16 {%0,%1,%2,%3}, [%4];"
                 : "=r"(r[0]), "=r"(r[1]), "=r"(r[2]), "=r"(r[3]) : "r"(a) : "memory");
}
__device__ __forceinline__ void mma16816(float (&c)[4], const uint32_t (&a)[4], uint32_t b0, uint32_t b1) {
    asm volatile("mma.sync.aligned.m16n8k16.row.col.f32.bf16.bf16.f32 {%0,%1,%2,%3}, {%4,%5,%6,%7}, {%8,%9}, {%0,%1,%2,%3};"
                 : "+f"(c[0]), "+f"(c[1]), "+f"(c[2]), "+f"(c[3])
                 : "r"(a[0]), "r"(a[1]), "r"(a[2]), "r"(a[3]), "r"(b0), "r"(b1));
}
__device__ __forceinline__ uint32_t lds32(uint32_t a) {
    uint32_t r; asm volatile("ld.shared.b32 %0, [%1];" : "=r"(r) : "r"(a) : "memory"); return r;
}
__device__ __forceinline__ uint32_t lds16(uint32_t a) {
    unsigned short r; asm volatile("ld.shared.b16 %0, [%1];" : "=h"(r) : "r"(a) : "memory"); return r;
}
__device__ __forceinline__ float ldsf(uint32_t a) { return __uint_as_float(lds32(a)); }
__device__ __forceinline__ uint4 lds128(uint32_t a) {
    uint4 r; asm volatile("ld.shared.v4.b32 {%0,%1,%2,%3}, [%4];" : "=r"(r.x), "=r"(r.y), "=r"(r.z), "=r"(r.w) : "r"(a) : "memory"); return r;
}
__device__ __forceinline__ float4 lds128f(uint32_t a) {
    float4 r; asm volatile("ld.shared.v4.f32 {%0,%1,%2,%3}, [%4];" : "=f"(r.x), "=f"(r.y), "=f"(r.z), "=f"(r.w) : "r"(a) : "memory"); return r;
}
__device__ __forceinline__ void sts16(uint32_t a, uint32_t v) { asm volatile("st.shared.b16 [%0], %1;" ::"r"(a), "h"((unsigned short)v) : "memory"); }
__device__ __forceinline__ void sts32(uint32_t a, uint32_t v) { asm volatile("st.shared.b32 [%0], %1;" ::"r"(a), "r"(v) : "memory"); }
__device__ __forceinline__ void sts64(uint32_t a, uint32_t x, uint32_t y) { asm volatile("st.shared.v2.b32 [%0], {%1,%2};" ::"r"(a), "r"(x), "r"(y) : "memory"); }
__device__ __forceinline__ void sts64_if(bool p, uint32_t a, float x, float y) {
    asm volatile("{\n.reg .pred q;\nsetp.ne.u32 q, %3, 0;\n@q st.shared.v2.f32 [%0], {%1,%2};\n}" ::"r"(a), "f"(x), "f"(y), "r"((uint32_t)p) : "memory");
}
__device__ __forceinline__ void stsf(uint32_t a, float v) { sts32(a, __float_as_uint(v)); }
__device__ __forceinline__ void sts128(uint32_t a, uint4 v) {
    asm volatile("st.shared.v4.b32 [%0], {%1,%2,%3,%4};" ::"r"(a), "r"(v.x), "r"(v.y), "r"(v.z), "r"(v.w) : "memory");
}
__device__ __forceinline__ void sts128f(uint32_t a, float x, float y, float z, float w) {
    asm volatile("st.shared.v4.f32 [%0], {%1,%2,%3,%4};" ::"r"(a), "f"(x), "f"(y), "f"(z), "f"(w) : "memory");
}
__device__ __forceinline__ float4 sum8(uint32_t a, int st) {
    float4 v[8];
#pragma unroll
    for (int w = 0; w < 8; w++) v[w] = lds128f(a + w * st);
#pragma unroll
    for (int o = 4; o; o >>= 1)
#pragma unroll
        for (int w = 0; w < o; w++) { v[w].x += v[w + o].x; v[w].y += v[w + o].y; v[w].z += v[w + o].z; v[w].w += v[w + o].w; }
    return v[0];
}
__device__ __forceinline__ void pub32(bool p, void* a, uint32_t v) {
    asm volatile("{\n.reg .pred q;\nsetp.ne.u32 q, %2, 0;\n@q st.relaxed.gpu.global.b32 [%0], %1;\n}" ::"l"(a), "r"(v), "r"((uint32_t)p) : "memory");
}
__device__ __forceinline__ void pub64(bool p, void* a, uint32_t x, uint32_t y) {
    asm volatile("{\n.reg .pred q;\nsetp.ne.u32 q, %3, 0;\n@q st.relaxed.gpu.global.v2.b32 [%0], {%1,%2};\n}" ::"l"(a), "r"(x), "r"(y), "r"((uint32_t)p) : "memory");
}
__device__ __forceinline__ void st16(bool p, void* a, uint32_t v) {
    asm volatile("{\n.reg .pred q;\nsetp.ne.u32 q, %2, 0;\n@q st.global.b16 [%0], %1;\n}" ::"l"(a), "h"((unsigned short)v), "r"((uint32_t)p) : "memory");
}
__device__ __forceinline__ void clr128(bool p, void* a) {
    asm volatile("{\n.reg .pred q;\nsetp.ne.u32 q, %1, 0;\n@q st.relaxed.gpu.global.v4.b32 [%0], {%2,%2,%2,%2};\n}" ::"l"(a), "r"((uint32_t)p), "r"(0) : "memory");
}
__device__ __forceinline__ uint32_t back32(bool p, const void* a) {
    uint32_t r = 0;
    asm volatile("{\n.reg .pred q;\nsetp.ne.u32 q, %2, 0;\n@q ld.relaxed.gpu.global.b32 %0, [%1];\n}" : "+r"(r) : "l"(a), "r"((uint32_t)p) : "memory");
    return r;
}
__device__ __forceinline__ void ldg_missing(uint4& r, const uint4* p, uint32_t lo) {
    asm volatile("{\n.reg .pred q;\nsetp.eq.u32 q, %5, 0;\n@q ld.relaxed.gpu.global.v4.b32 {%0,%1,%2,%3}, [%4];\n}"
                 : "+r"(r.x), "+r"(r.y), "+r"(r.z), "+r"(r.w) : "l"(p), "r"(lo) : "memory");
}
__device__ __forceinline__ uint32_t min4(const uint4& v) { return min(min(v.x, v.y), min(v.z, v.w)); }
template <int N, int SLEEP, class Side>
__device__ __forceinline__ void poll(uint4 (&v)[N], const uint4* p, int stride, uint32_t skip, Side side) {
    uint32_t lo[N];
#pragma unroll
    for (int i = 0; i < N; i++) { lo[i] = (skip >> i) & 1; v[i] = make_uint4(lo[i], lo[i], lo[i], lo[i]); }
#pragma unroll 1
    for (unsigned it = 0;; it++) {
#pragma unroll
        for (int i = 0; i < N; i++) ldg_missing(v[i], p + i * stride, lo[i]);
        side();
        uint32_t all = 0xFFFFFFFFu;
#pragma unroll
        for (int i = 0; i < N; i++) { lo[i] = min4(v[i]); all = min(all, lo[i]); }
        if (__all_sync(0xffffffffu, all != 0)) break;
        if (it > SPIN_LIMIT) __trap();
        if (SLEEP) __nanosleep(SLEEP);
    }
}
template <int N, int SLEEP>
__device__ __forceinline__ void poll(uint4 (&v)[N], const uint4* p, int stride) { poll<N, SLEEP>(v, p, stride, 0, [] {}); }
__device__ __forceinline__ uint4 unzip(const uint4& e) {
    uint4 r;
    r.x = ~__byte_perm(e.x, e.z, 0x5410);
    r.y = ~__byte_perm(e.x, e.z, 0x7632);
    r.z = ~__byte_perm(e.y, e.w, 0x5410);
    r.w = ~__byte_perm(e.y, e.w, 0x7632);
    return r;
}
__device__ __forceinline__ void put_piece(const uint4& e, uint32_t a) {
    const uint4 u = unzip(e);
    sts32(a, u.x); sts32(a + AV_PITCH, u.y); sts32(a + 2 * AV_PITCH, u.z); sts32(a + 3 * AV_PITCH, u.w);
}
template <int SLEEP, class Side>
__device__ __forceinline__ void gather576(const uint4* src, uint32_t dst, int warp, int tid, Side side) {
    uint4 v[2];
    poll<2, SLEEP>(v, src + tid, 96, warp == 5 ? 0 : 2, side);
    put_piece(v[0], dst + tid * 4);
    if (warp == 5) put_piece(v[1], dst + tid * 4 + 384);
}
__device__ __forceinline__ float ln_rden(float var) { return rcp(bfr(fsqrt(bfr(bfr(fmaxf(var, 0.f)) + 1e-5f)))); }
__device__ __forceinline__ void ln_stats(const uint32_t (&w)[9], float& mean_b, float& rden) {
    const float piv = __shfl_sync(0xffffffffu, bf_lo(w[0]), 0);
    float s = 0.f, q = 0.f;
#pragma unroll
    for (int i = 0; i < 9; i++) {
        const float a = bf_lo(w[i]) - piv, c = bf_hi(w[i]) - piv;
        s += a + c;
        q = fmaf(a, a, fmaf(c, c, q));
    }
#pragma unroll
    for (int o = 16; o; o >>= 1) { s += __shfl_xor_sync(0xffffffffu, s, o); q += __shfl_xor_sync(0xffffffffu, q, o); }
    s *= (1.0f / D_MODEL);
    mean_b = bfr(piv + s);
    rden = ln_rden(fmaf(q, 1.0f / D_MODEL, -s * s));
}
__device__ __forceinline__ float ln_mod(float x, float mean_b, float rden, float scale1, float shift) {
    return bfr(bfr(bfr(x - mean_b) * rden) * scale1) + shift;
}

__device__ __forceinline__ uint32_t ln_mod2(uint32_t x, uint32_t mean2, float rden, uint32_t scale1, uint32_t shift) {
    const uint32_t d = sub2(x, mean2);
    return add2(mul2(pack_bf(bf_lo(d) * rden, bf_hi(d) * rden), scale1), shift);
}

__global__ void __launch_bounds__(NTHREADS, 1)
fused_block_kernel(const __grid_constant__ Params prm, const __nv_bfloat16* __restrict__ x, const __nv_bfloat16* __restrict__ cvec,
                   __nv_bfloat16* __restrict__ out, uint4* __restrict__ scr, const void* __restrict__ plan) {
    extern __shared__ __align__(1024) unsigned char smem_raw[];
    const uint32_t sm = (uint32_t)__cvta_generic_to_shared(smem_raw);
    const uint32_t bars = sm + SM_BAR;
    const int tid = threadIdx.x, cta = blockIdx.x;
    const int g = cta >> 3, j = cta & 7;
    auto kv_row = [&](int n) { return ((n >> 3) * 16 + g) * SK + ((n & 7) * 8 + j) * 64; };
    uint64_t pol;
    asm volatile("createpolicy.fractional.L2::evict_first.b64 %0, 1.0;" : "=l"(pol));
    if (tid == 0) {
        mbar_init(bars + CH_KV * 8, 1);
        asm volatile("fence.mbarrier_init.release.cluster;" ::: "memory");
        mbar_expect(bars + CH_KV * 8, TILE_BYTES);
        tma3(sm, &prm.m[M_K], 0, kv_row(0), 0, bars + CH_KV * 8, pol);
    }
    const int warp = __shfl_sync(0xffffffffu, tid >> 5, 0), lane = tid & 31;
    const int f0 = (g >> 1) * 576 + j * 64, fx = (g >> 1) * 576 + 448 + j * 16;
    const bool xg = j >= 4;

    if (warp >= 8) {
    if (warp == 8) {
        if (lane == 0) {
#pragma unroll
            for (int n = 0; n < 3; n++) mbar_init(bars + n * 8, 1);
            asm volatile("fence.mbarrier_init.release.cluster;" ::: "memory");
#pragma unroll
            for (int n = 0; n < 3; n++) {
                mbar_expect(bars + n * 8, cta < 108 ? 12288 : 0);
                if (cta < 108) tma3(sm + SM_W0 + n * 12288, &prm.m[M_WMOD], (cta % 36) * 16, n * 192, (cta / 36) * 2, bars + n * 8, pol);
            }
#pragma unroll
            for (int n = 3; n < 6 + NHARD; n++) if (n != CH_KV) mbar_init(bars + n * 8, 1);
            asm volatile("fence.mbarrier_init.release.cluster;" ::: "memory");
        }
        __syncwarp();
        asm volatile("bar.arrive 5, %0;" ::"n"(NTHREADS) : "memory");
        asm volatile("bar.sync 4, 96;" ::: "memory");
        if (lane == 0) {
#pragma unroll 1
            for (int n = 0; n < 3; n++) {
                mbar_expect(bars + (3 + n) * 8, 12288);
                mbar_wait(bars + n * 8);
                tma3(sm + SM_W0 + (3 + n) * 12288, &prm.m[M_WQ], cta * 32, n * 192, 0, bars + (3 + n) * 8, pol);
            }
#pragma unroll 1
            for (int n = 1; n < NHARD; n++) {
                mbar_expect(bars + (CH_KV + n) * 8, TILE_BYTES);
                mbar_wait(bars + (n == 1 ? CH_KV : n + 2) * 8);
                tma3(sm + n * TILE_BYTES, &prm.m[M_K], 0, kv_row(n), 0, bars + (CH_KV + n) * 8, pol);
            }
        }
        __syncwarp();
        asm volatile("bar.sync 2, 64;" ::: "memory");
        if (sm & 1023) __trap();
        uint4 e = lds128(sm + SM_TAB + (6 + NHARD) * 16);
#pragma unroll 1
        for (int p = 6 + NHARD; p < NCHUNK; p++) {
            const uint4 nx = lds128(sm + SM_TAB + (p + 1) * 16);
            if (e.x & 0x80000u) {
                const uint32_t tb = bars + ((e.w >> ((lane & 3) * 8)) & 255) * 8;
#pragma unroll 1
                for (unsigned it = 0;; it++) {
                    const bool far = lds32(sm + SM_ADJ) >= (e.y >> 16);
                    if (__all_sync(0xffffffffu, mbar_test(tb) || ((lane & 3) == 3 && far))) break;
                    if (it > 16 * SPIN_LIMIT) __trap();
                }
                if (lane == 0) {
                    tma3(sm + (e.x & 0x7FFFF), &prm.m[(e.x >> 20) & 15], e.y & 0xFFFF, e.z & 0x3FFFF, 0, bars + (e.x >> 24) * 8, pol);
                }
            }
            e = nx;
        }
    } else if (warp == 9) {
        if (lane < NMAPS)
            sts64(sm + SM_ORG + lane * 8,
                  lane <= M_V ? 0 : lane <= M_WQ ? cta * 32 : lane <= M_WD ? j * 64 : lane <= M_WU ? f0 : lane <= M_WDX ? 512 + j * 16 : fx,
                  (lane & 2) ? 0 : (lane & 1) ? g * 288 : g * 256);
        if (lane == 0) sts32(sm + SM_ADJ, 0);
        uint4 pe[4];
#pragma unroll
        for (int i = 0; i < 4; i++) pe[i] = __ldg(reinterpret_cast<const uint4*>(plan) + min(lane + 32 * i, NCHUNK - 1));
        if (lane == 0) {
#pragma unroll
            for (int n = 6 + NHARD; n < NBAR; n++) mbar_init(bars + n * 8, n >= REL && n < RELW ? 2 : 1);
            asm volatile("fence.mbarrier_init.release.cluster;" ::: "memory");
        }
        __syncwarp();
        asm volatile("bar.arrive 5, %0;" ::"n"(NTHREADS) : "memory");
        asm volatile("bar.sync 4, 96;" ::: "memory");
#pragma unroll
        for (int i = 0; i < 4; i++) {
            if ((pe[i].y >> 16) == 0) {
                const uint32_t t = pe[i].y, h = t & 1;
                pe[i].x += xg ? (t - 2) * 6144 + (M_WGX << 20) : t < 2 ? h * 4096 + (M_WOX << 20) : 8192 + h * 4608 + (M_WDX << 20);
                pe[i].y = xg ? (t - 2 < 3 ? (t - 2) * 192 + (6144 << 16) : 0)
                             : t < 2 ? h * 128 + (4096 << 16) : t >= 4 ? h * 144 + (4608 << 16) : 0;
            }
            if (((pe[i].x >> 20) & 3) == 2 && (pe[i].x >> 24) >= CH_WO) pe[i].x += (g & 1) << 20;
            const int p = lane + 32 * i;
            if (p < NCHUNK) {
                const uint32_t org = sm + SM_ORG + ((pe[i].x >> 20) & 15) * 8;
                if (p >= 6 + NHARD) mbar_expect(bars + (pe[i].x >> 24) * 8, pe[i].y >> 16);
                sts128(sm + SM_TAB + p * 16, make_uint4(pe[i].x | ((pe[i].y >> 16) ? 0x80000u : 0u), lds32(org) | (pe[i].z << 16),
                                                        (((pe[i].x >> 20) & 15) <= M_V ? kv_row(pe[i].y & 0xFFFF) : lds32(org + 4) + (pe[i].y & 0xFFFF)) | (pe[i].z & 0xFFFC0000u), pe[i].w));
            }
        }
        asm volatile("bar.arrive 2, 64;" ::: "memory");
        __syncwarp();
        if (lane < NMAPS) asm volatile("prefetch.tensormap [%0];" ::"l"(&prm.m[lane]) : "memory");
        if (lane == 0) {
            int n = 0;
            uint32_t kb = 0;
#pragma unroll 1
            for (unsigned it = 0; n < NCHUNK; it++) {
                while (n < NCHUNK && mbar_test(bars + (lds32(sm + SM_TAB + n * 16) >> 24) * 8)) n++;
                const uint32_t now = n == NCHUNK ? 2048 : n ? lds32(sm + SM_TAB + n * 16 - 8) >> 18 : 0;
                const uint32_t all = now == kb ? back32(true, scr + G_CNT) : atomicAdd(reinterpret_cast<unsigned*>(scr + G_CNT), now - kb);
                sts32(sm + SM_ADJ, all / NCTA);
                pub32(all + now - kb == NCTA * 2048, scr + G_CNT, 0);
                kb = now;
                if (it > SPIN_LIMIT) __trap();
            }
        }
    }
    } else {
    if (warp == 0) asm volatile("bar.arrive 4, 96;" ::: "memory");
    uint2 cw[3];
    uint32_t xw[9];
#pragma unroll
    for (int i = 0; i < 3; i++) cw[i] = cta < 108 ? __ldg(reinterpret_cast<const uint2*>(cvec) + min(tid + 256 * i, 575)) : make_uint2(0, 0);
#pragma unroll
    for (int i = 0; i < 9; i++) xw[i] = cta < 36 && warp >= 4 ? __ldg(reinterpret_cast<const uint32_t*>(x) + (warp & 3) * 288 + lane + 32 * i) : 0u;
    clr128(cta < 32 && tid < 64, scr + (G_Q + cta * 64 + tid));
    uint32_t cleared = back32(cta < 32 && tid < 64, scr + (G_Q + cta * 64 + tid));
    const int mi = lane >> 3, r8 = lane & 7;
    const uint32_t bfrag = ((lane >> 2) & 3) * AV_PITCH + (lane & 3) * 4;
    uint32_t* const scr32 = reinterpret_cast<uint32_t*>(scr);
    uint2* const scr64 = reinterpret_cast<uint2*>(scr);
    const int pr = warp >> 1, hf = warp & 1;

#pragma unroll
    for (int i = 0; i < 3; i++) {
        const int p = min(tid + 256 * i, 575);
        const float a0 = bf_lo(cw[i].x), a1 = bf_hi(cw[i].x), a2 = bf_lo(cw[i].y), a3 = bf_hi(cw[i].y);
        sts64(sm + SM_AVA + (p / 144) * AV_PITCH + (p % 144) * 8, pack_bf(a0 * sigm(a0), a1 * sigm(a1)), pack_bf(a2 * sigm(a2), a3 * sigm(a3)));
    }
    if (cta < 36 && warp >= 4) {
        float mean_b, rden;
        ln_stats(xw, mean_b, rden);
        if (lane == 0) sts64(sm + SM_QS + (warp & 3) * 8, __float_as_uint(mean_b), __float_as_uint(rden));
#pragma unroll
        for (int i = 0; i < 9; i++) sts32(sm + SM_CB1 + (warp & 3) * 1152 + (lane + 32 * i) * 4, xw[i]);
    }
    if (cleared) __trap();
    uint32_t mod_lo = 0, mod_hi = 0;
#pragma unroll 1
    for (int it = 0; it < 2; it++) {
        if (it == 1) gather576<300>(scr + (G_H + (g % NREP) * 288), sm + SM_AVB, warp, tid, [] {});
        if (it) cbar(); else asm volatile("bar.sync 5, %0;" ::"n"(NTHREADS) : "memory");
        if (cta < 108 || it == 1) {
            const int k = (mi >> 1) * 8 + r8;
            const uint32_t base = sm + SM_W0 + (it ? 36864 + k * 64 : (mi & 1) * 6144 + k * 32);
            const uint32_t ch = it ? (((mi & 1) * 2) ^ (r8 >> 1)) : (r8 >> 2);
            const uint32_t a0 = base + (ch << 4), a1 = base + ((ch ^ 1) << 4), kb = it ? 1024 : 512;
            const uint32_t bb = sm + (it ? SM_AVB : SM_AVA) + bfrag + warp * 32;
            float c0[4] = {0.f, 0.f, 0.f, 0.f}, c1[4] = {0.f, 0.f, 0.f, 0.f};
            uint32_t bq[5][2];
#pragma unroll
            for (int i = 0; i < 5; i++) { bq[i][0] = lds32(bb + i * 256); bq[i][1] = lds32(bb + i * 256 + 16); }
            if (warp >= 4) bq[4][0] = bq[4][1] = 0;
#pragma unroll
            for (int i = 0; i < 3; i++) mbar_wait(bars + (it * 3 + i) * 8);
#pragma unroll
            for (int i = 0; i < 5; i++) {
                const int ks = min(warp + 8 * i, 35);
                const int cq = ks / 12;
                const uint32_t off = cq * 12288 + (ks - cq * 12) * kb;
                uint32_t u[4], v[4];
                ldsm4t(u, a0 + off);
                ldsm4t(v, a1 + off);
                mma16816(c0, u, bq[i][0], bq[i][1]);
                mma16816(c1, v, bq[i][0], bq[i][1]);
            }
            const bool t1 = (lane & 2) != 0;
            sts128f(sm + SM_RED + warp * 512 + (t1 ? 256 : 0) + ((lane >> 2) * 2 + (lane & 1)) * 16,
                    t1 ? c1[0] : c0[0], t1 ? c1[1] : c0[1], t1 ? c1[2] : c0[2], t1 ? c1[3] : c0[3]);
            cbar();
            if (warp == 7) {
                const float4 r = sum8(sm + SM_RED + lane * 16, 512);
                if (it == 0 && cta < 36) {
                    const uint32_t xp = sm + SM_CB1 + (lane & 1) * 2304 + (cta * 16 + (lane >> 1)) * 2;
                    const float4 st = lds128f(sm + SM_QS + (lane & 1) * 16);
                    const float h0 = ln_mod(bf_lo(lds16(xp)), st.x, st.y, bfr(1.0f + bfr(r.z)), bfr(r.x));
                    const float h1 = ln_mod(bf_lo(lds16(xp + 1152)), st.z, st.w, bfr(1.0f + bfr(r.w)), bfr(r.y));
                    const uint32_t hv = enc(pack_bf(h0, h1));
#pragma unroll
                    for (int i = 0; i < NREP; i++) pub32(true, scr32 + (G_H * 4 + i * 1152 + cta * 32 + lane), hv);
                } else {
                    const uint32_t lo = enc(pack_bf(r.x, r.y)), hi = enc(pack_bf(r.z, r.w));
                    pub32(it, scr32 + (G_Q * 4 + cta * 64 + lane), lo);
                    pub32(it, scr32 + (G_Q * 4 + cta * 64 + 32 + lane), hi);
                    if (it == 0) { mod_lo = lo; mod_hi = hi; }
                }
            }
        }
        if (tid == 192) mbar_arrive(bars + (RELW + it) * 8);
    }

    {
        constexpr int PER = (G_TOTAL - G_STAT + 71) / 72;
        static_assert(PER <= 1024, "clear split");
        const int i = G_STAT + max(cta - 36, 0) * PER + tid, end = cta < 36 ? 0 : min(i - tid + PER, G_TOTAL);
#pragma unroll
        for (int k = 0; k < 1024; k += 256) clr128(i + k < end, scr + i + k);
#pragma unroll
        for (int k = 0; k < 1024; k += 256) cleared |= back32(i + k < end, scr + i + k);
    }
    if (tid < 128) {
        uint4 v[1];
        poll<1, 40>(v, scr + (G_Q + g * 128 + tid), 0);
        put_piece(v[0], sm + SM_AVA + tid * 4);
    }
    if (cleared) __trap();
    cbar();
    if (warp == 7) {
        uint32_t* dst = scr32 + (G_MOD * 4 + ((cta / 72) * 1152 + (cta % 36) * 16) * 2 + lane);
        pub32(cta >= 36 && cta < 108, dst, mod_lo);
        pub32(cta >= 36 && cta < 108, dst + 1152, mod_hi);
    }
    {
        auto fetch_mod = [&]() {
            if (warp < 5) {
            const int t = min(tid, 143);
            uint4 v[4];
            poll<4, 40>(v, scr + (G_MOD + 288 + t), 144);
#pragma unroll
            for (int i = 0; i < 4; i++) {
                uint4 u = unzip(v[i]);
                if (i >= 2) {
                    u.x = pack_bf(1.0f + bf_lo(u.x), 1.0f + bf_hi(u.x)); u.y = pack_bf(1.0f + bf_lo(u.y), 1.0f + bf_hi(u.y));
                    u.z = pack_bf(1.0f + bf_lo(u.z), 1.0f + bf_hi(u.z)); u.w = pack_bf(1.0f + bf_lo(u.w), 1.0f + bf_hi(u.w));
                }
                const uint32_t d = sm + (i >= 2 ? SM_CB1 : SM_SB) + (t + 144 * (i & 1)) * 4;
                sts32(d, u.x); sts32(d + AV_PITCH, u.y); sts32(d + 2 * AV_PITCH, u.z); sts32(d + 3 * AV_PITCH, u.w);
            }
        } else if (warp == 7 && cta < 72) {
            sts16(sm + SM_XR + (lane & 7) * 8 + (lane >> 3) * 2,
                  reinterpret_cast<const unsigned short*>(x)[(lane >> 3) * D_MODEL + cta * 8 + (lane & 7)]);
            uint4 v[2];
            poll<2, 40>(v, scr + (G_MOD + cta * 4 + ((lane & 7) >> 1)), 864);
            sts128(sm + SM_QS + (lane & 7) * 16, make_uint4(~((lane & 1) ? v[0].z : v[0].x), ~((lane & 1) ? v[0].w : v[0].y),
                                                            ~((lane & 1) ? v[1].z : v[1].x), ~((lane & 1) ? v[1].w : v[1].y)));
        }
        };
        const uint32_t koff = (hf * 32 + (mi & 1) * 8 + r8) * 128;
        uint32_t sw[4];
#pragma unroll
        for (int c = 0; c < 4; c++) sw[c] = koff + (((2 * c + (mi >> 1)) ^ r8) << 4);
#pragma unroll 1
        for (int i = pr; i < TILES; i += 4) {
            uint32_t qf[8][2];
#pragma unroll
            for (int ks = 0; ks < 8; ks++) {
                const uint32_t a = sm + SM_AVA + (i >> 3) * AV_PITCH + ((lane >> 2) & 1) * 256 + ks * 32 + (lane & 3) * 4;
                qf[ks][0] = lds32(a); qf[ks][1] = lds32(a + 16);
            }
            mbar_wait(bars + (CH_KV + i) * 8);
            const uint32_t tb = sm + (i % NSLOT) * TILE_BYTES;
            float c[4][4];
#pragma unroll
            for (int u = 0; u < 4; u++) { c[u][0] = c[u][1] = c[u][2] = c[u][3] = 0.f; }
#pragma unroll
            for (int ks = 0; ks < 4; ks++) {
#pragma unroll
                for (int u = 0; u < 4; u++) {
                    uint32_t a[4];
                    ldsm4(a, tb + (u >> 1) * 8192 + (u & 1) * 2048 + sw[ks]);
                    mma16816(c[u], a, qf[(u >> 1) * 4 + ks][0], qf[(u >> 1) * 4 + ks][1]);
                }
            }
            __syncwarp();
            if (lane == 0) mbar_arrive(bars + (REL + i) * 8);
            const bool t1 = (lane & 2) != 0, hi = (lane & 1) != 0;
            const float p0 = t1 ? (hi ? c[1][2] + c[3][2] : c[1][0] + c[3][0]) : (hi ? c[0][2] + c[2][2] : c[0][0] + c[2][0]);
            const float p1 = t1 ? (hi ? c[1][3] + c[3][3] : c[1][1] + c[3][1]) : (hi ? c[0][3] + c[2][3] : c[0][1] + c[2][1]);
            const uint32_t w = pack_bf(bfr(p0) * 0.08838834764831845f, bfr(p1) * 0.08838834764831845f);
            const uint32_t a = sm + SM_SC + (i * 64 + hf * 32 + (lane & 3) * 8 + (lane >> 2)) * 2;
            sts16(a, w & 0xFFFFu);
            sts16(a + 4096, w >> 16);
            if ((i >> 2) == 4 + cta % 3) fetch_mod();
        }
    }
    cbar();

    {
        const uint32_t a = sm + SM_SC + tid * 32;
        const uint4 u0 = lds128(a), u1 = lds128(a + 16);
        const uint32_t w[8] = {u0.x, u0.y, u0.z, u0.w, u1.x, u1.y, u1.z, u1.w};
        float e[16], m = -INFINITY;
#pragma unroll
        for (int i = 0; i < 8; i++) { e[2 * i] = bf_lo(w[i]); e[2 * i + 1] = bf_hi(w[i]); m = fmaxf(m, fmaxf(e[2 * i], e[2 * i + 1])); }
#pragma unroll
        for (int o = 16; o; o >>= 1) m = fmaxf(m, __shfl_xor_sync(0xffffffffu, m, o));
        float l = 0.f;
#pragma unroll
        for (int i = 0; i < 16; i++) { e[i] = ex2((e[i] - m) * LOG2E); l += e[i]; }
#pragma unroll
        for (int o = 16; o; o >>= 1) l += __shfl_xor_sync(0xffffffffu, l, o);
        if (lane == 0) sts64(sm + SM_RED + warp * 8, encf(m), encf(l));
        cbar();
        if (warp == 0) {
            pub32(lane < 16, scr32 + (G_STAT * 4 + cta * 32 + lane), lds32(sm + SM_RED + (lane & 15) * 4));
            uint4 v[1];
            poll<1, 40>(v, scr + (G_STAT + (g * 8 + (lane >> 2)) * 8 + (lane & 3)), 0);
            const float ma = decf(v[0].x), mb = decf(v[0].z);
            float ga = ma, gb = mb;
#pragma unroll
            for (int o = 4; o < 32; o <<= 1) { ga = fmaxf(ga, __shfl_xor_sync(0xffffffffu, ga, o)); gb = fmaxf(gb, __shfl_xor_sync(0xffffffffu, gb, o)); }
            float la = decf(v[0].y) * ex2((ma - ga) * LOG2E), lb = decf(v[0].w) * ex2((mb - gb) * LOG2E);
#pragma unroll
            for (int o = 4; o < 32; o <<= 1) { la += __shfl_xor_sync(0xffffffffu, la, o); lb += __shfl_xor_sync(0xffffffffu, lb, o); }
            sts128f(sm + SM_RED + 64 + (lane & 3) * 16, ga, rcp(la), gb, rcp(lb));
        }
        cbar();
        const float f = ex2((m - ldsf(sm + SM_RED + 64 + warp * 8)) * LOG2E) * ldsf(sm + SM_RED + 68 + warp * 8);
        uint4 o0, o1;
        o0.x = pack_bf(e[0] * f, e[1] * f); o0.y = pack_bf(e[2] * f, e[3] * f); o0.z = pack_bf(e[4] * f, e[5] * f); o0.w = pack_bf(e[6] * f, e[7] * f);
        o1.x = pack_bf(e[8] * f, e[9] * f); o1.y = pack_bf(e[10] * f, e[11] * f); o1.z = pack_bf(e[12] * f, e[13] * f); o1.w = pack_bf(e[14] * f, e[15] * f);
        sts128(a, o0); sts128(a + 16, o1);
        cbar();
    }

    uint32_t wa[2][18][4];
    const bool pw = warp < 4 || (warp == 4 && j < 4);
    const uint32_t astep = warp < 4 ? 2048 : 512;
    const uint32_t aoff = warp < 4 ? ((mi >> 1) * 8 + r8) * 128 + (((warp * 2 + (mi & 1)) ^ r8) << 4)
                                   : ((mi >> 1) * 8 + r8) * 32 + (((mi & 1) ^ (r8 >> 2)) << 4);
    const uint32_t abase[2] = {sm + (warp < 4 ? SM_WO : SM_X) + aoff, sm + (warp < 4 ? SM_WD : SM_X + 8192) + aoff};
    int nl = 0;
    auto proj_bar = [&](int rd) {
        const int c = min(lane, 3 + 2 * rd);
        return bars + (warp < 4 ? (rd ? CH_WD : CH_WO) + c : CH_X + 4 * rd + c / (2 + rd)) * 8;
    };
    auto proj_more = [&](int rd, bool t) {
        const int nr = min(__ffs(~__ballot_sync(0xffffffffu, t) | 0x100) - 1, 4 + 2 * rd);
        if (nr > nl) {
#pragma unroll
            for (int c = 0; c < 4 + 2 * rd; c++) {
                if (c >= nl && c < nr) {
#pragma unroll
                    for (int u = c * (4 - rd); u < (c + 1) * (4 - rd); u++) ldsm4t(wa[rd][u], abase[rd] + u * astep);
                }
            }
            nl = nr;
        }
    };
    {
        float o[4][4];
#pragma unroll
        for (int u = 0; u < 4; u++) { o[u][0] = o[u][1] = o[u][2] = o[u][3] = 0.f; }
        const uint32_t voff = hf * 8192 + ((mi >> 1) * 8 + r8) * 128;
        uint32_t sw[4];
#pragma unroll
        for (int u = 0; u < 4; u++) sw[u] = voff + (((2 * u + (mi & 1)) ^ r8) << 4);
        const uint32_t pb = sm + SM_SC + ((lane >> 2) & 1) * 4096 + (lane & 3) * 4 - TILES * 128;
        auto v_tile = [&](int i) {
            uint32_t pf[4][2];
#pragma unroll
            for (int kk = 0; kk < 4; kk++) { pf[kk][0] = lds32(pb + i * 128 + kk * 32); pf[kk][1] = lds32(pb + i * 128 + kk * 32 + 16); }
            const uint32_t tb = sm + (i % NSLOT) * TILE_BYTES;
            mbar_wait(bars + (CH_KV + i) * 8);
#pragma unroll
            for (int kk = 0; kk < 4; kk++) {
#pragma unroll
                for (int u = 0; u < 4; u++) {
                    uint32_t a[4];
                    ldsm4t(a, tb + kk * 2048 + sw[u]);
                    mma16816(o[u], a, pf[kk][0], pf[kk][1]);
                }
            }
            __syncwarp();
            if (lane == 0) mbar_arrive(bars + (REL + i) * 8);
        };
#pragma unroll 1
        for (int t = 0; t <= 8; t++) {
            const int gb = t == 8 ? 3 : (t & 1) ? (t - 3) >> 1 : -1;
            bool todo = t < 8;
            uint4 v[2];
            poll<2, 0>(v, scr + (G_OPART + (gb * NCTA + g * 8 + (lane & 3) * 2) * 64 + (tid >> 2)), 64, gb < 0 ? 3 : 0, [&] {
                if (todo) {
                v_tile(TILES + pr + 4 * t);
            if (t & 1) {
                const int u = lane & 3;
                const uint32_t red = sm + ((t & 2) ? SM_RED : SM_AVB);
                const uint32_t a = red + pr * 1024 + (hf * 64 + u * 16 + (lane >> 2)) * 4;
                float w[4];
#pragma unroll
                for (int q = 0; q < 4; q++) w[q] = u == 0 ? o[0][q] : u == 1 ? o[1][q] : u == 2 ? o[2][q] : o[3][q];
                stsf(a, w[0]); stsf(a + 512, w[1]); stsf(a + 32, w[2]); stsf(a + 512 + 32, w[3]);
#pragma unroll
                for (int q = 0; q < 4; q++) { o[q][0] = o[q][1] = o[q][2] = o[q][3] = 0.f; }
                cbar();
                const uint32_t r = red + tid * 4;
                pub32(true, scr32 + (G_OPART * 4 + ((t >> 1) * NCTA + cta) * 256 + tid),
                      encf((ldsf(r) + ldsf(r + 1024)) + (ldsf(r + 2048) + ldsf(r + 3072))));
            }
                } else if (warp < 5 && nl < 4) proj_more(0, mbar_test(proj_bar(0)));
                todo = false;
            });
            if (gb >= 0) {
                const bool od = lane & 1;
                const float s0 = decf(v[0].x) + decf(v[1].x), s1 = decf(v[0].y) + decf(v[1].y);
                const float s2 = decf(v[0].z) + decf(v[1].z), s3 = decf(v[0].w) + decf(v[1].w);
                float a0 = (od ? s2 : s0) + __shfl_xor_sync(0xffffffffu, od ? s0 : s2, 1);
                float a1 = (od ? s3 : s1) + __shfl_xor_sync(0xffffffffu, od ? s1 : s3, 1);
                a0 += __shfl_xor_sync(0xffffffffu, a0, 2);
                a1 += __shfl_xor_sync(0xffffffffu, a1, 2);
                sts32(sm + SM_AVA + gb * AV_PITCH + (tid >> 2) * 8 + (lane & 1) * 4, pack_bf(a0, a1));
            }
        }
    }

    auto project = [&](int rd) {
        uint32_t b4[9][4];
#pragma unroll
        for (int u = 0; u < 8 + rd; u++) ldsm4(b4[u], sm + SM_AVA + (r8 & 3) * AV_PITCH + mi * 16 + u * 64);
        if (__builtin_expect(nl < 4 + 2 * rd, 0)) {
#pragma unroll 1
            for (unsigned it = 0; nl < 4 + 2 * rd; it++) {
                proj_more(rd, mbar_test(proj_bar(rd)));
                if (it > 16 * SPIN_LIMIT) __trap();
            }
        }
        float c[4][4];
#pragma unroll
        for (int u = 0; u < 4; u++) { c[u][0] = c[u][1] = c[u][2] = c[u][3] = 0.f; }
#pragma unroll
        for (int u = 0; u < 16 + 2 * rd; u++) mma16816(c[u & 3], wa[rd][u], b4[u >> 1][(u & 1) * 2], b4[u >> 1][(u & 1) * 2 + 1]);
        const bool hi = (lane & 2) != 0;
        const int ob = (warp < 4 ? j * 8 + warp * 2 : 64 + j * 2) + (hi ? 1 : 0);
        pub64(pw, scr64 + ((G_PART + rd * 72 * 128 + (ob * 16 + g) * 8) * 2 + (lane >> 2) * 2 + (lane & 1)),
              encf(hi ? (c[2][2] + c[3][2]) + (c[0][2] + c[1][2]) : (c[2][0] + c[3][0]) + (c[0][0] + c[1][0])),
              encf(hi ? (c[2][3] + c[3][3]) + (c[0][3] + c[1][3]) : (c[2][1] + c[3][1]) + (c[0][1] + c[1][1])));
    };
    auto reduce = [&](int rd) {
        const uint32_t g01 = lds32(sm + SM_QS + (lane & 7) * 16 + rd * 8), g23 = lds32(sm + SM_QS + (lane & 7) * 16 + rd * 8 + 4);
        const uint32_t r01 = lds32(sm + SM_XR + (lane & 7) * 8), r23 = lds32(sm + SM_XR + 4 + (lane & 7) * 8);
        uint4 w[4];
        poll<4, 0>(w, scr + (G_PART + rd * 72 * 128 + cta * 128 + lane), 32);
        float t[4] = {(decf(w[0].x) + decf(w[1].x)) + (decf(w[2].x) + decf(w[3].x)), (decf(w[0].y) + decf(w[1].y)) + (decf(w[2].y) + decf(w[3].y)),
                      (decf(w[0].z) + decf(w[1].z)) + (decf(w[2].z) + decf(w[3].z)), (decf(w[0].w) + decf(w[1].w)) + (decf(w[2].w) + decf(w[3].w))};
#pragma unroll
        for (int q = 0; q < 4; q++) t[q] += __shfl_xor_sync(0xffffffffu, t[q], 8);
#pragma unroll
        for (int q = 0; q < 4; q++) t[q] += __shfl_xor_sync(0xffffffffu, t[q], 16);
        const uint32_t x01 = add2(r01, mul2(g01, pack_bf(t[0], t[1]))), x23 = add2(r23, mul2(g23, pack_bf(t[2], t[3])));
        if (rd == 1) {
            const uint32_t ov = (lane & 16) ? x23 : x01;
            st16(true, out + ((lane >> 3) * D_MODEL + cta * 8 + (lane & 7)), (lane & 8) ? ov >> 16 : ov);
        } else {
#pragma unroll
            for (int i = 0; i < NREP; i += 4)
                pub64(true, scr64 + (G_X1 * 2 + (i + (lane >> 3)) * 576 + cta * 8 + (lane & 7)), enc(x01), enc(x23));
            sts64(sm + SM_XR + (lane & 7) * 8, x01, x23);
        }
    };
    arrive_if<6>(warp >= 5);
    if (__builtin_expect(warp < 5, 1)) {
        await<6>();
        project(0);
    } else if (warp == 7 && cta < 72) {
        reduce(0);
    }
    {
        uint32_t wg[5][5][4];
        const bool four = warp >= 4;
        uint32_t gbar;
        {
            const int ks = min(warp + 8 * (lane >> 1), 35);
            gbar = bars + ((xg && (lane & 1)) ? CH_X + 2 + ks / 12 : CH_GU + ks / 3) * 8;
        }
        const int nw = four ? 4 : 5;
        auto gu_more = [&](bool t) {
            const int nr = min((__ffs(~__ballot_sync(0xffffffffu, t) | 0x400) - 1) >> 1, nw);
            if (nr > nl) {
#pragma unroll
                for (int i = 0; i < 5; i++) {
                    const int k = (warp + 8 * i) * 16 + (mi >> 1) * 8 + r8;
                    const uint32_t ag = sm + SM_WG + k * 128;
                    if (i >= nl && i < nr) {
#pragma unroll
                        for (int u = 0; u < 4; u++) ldsm4t(wg[i][u], ag + (((2 * u + (mi & 1)) ^ r8) << 4));
                        if (xg) ldsm4t(wg[i][4], sm + SM_X + k * 32 + (((mi & 1) ^ (r8 >> 2)) << 4));
                    }
                }
                nl = nr;
            }
        };
        nl = 0;
        gather576<0>(scr + (G_X1 + (g % NREP) * 288), sm + SM_AVB, warp, tid, [&] { if (nl < nw) gu_more(mbar_test(gbar)); });
        cbar();
        uint32_t bq[5][2];
        {
            const uint32_t fo = bfrag + warp * 32;
#pragma unroll
            for (int i = 0; i < 5; i++) { bq[i][0] = lds32(sm + SM_AVB + fo + i * 256); bq[i][1] = lds32(sm + SM_AVB + fo + i * 256 + 16); }
            const uint32_t piv2 = lane < 16 ? 0u : __byte_perm(lds32(sm + SM_AVB + ((lane >> 2) & 3) * AV_PITCH), 0, 0x1010);
            float m0[4] = {0.f, 0.f, 0.f, 0.f}, m1[4] = {0.f, 0.f, 0.f, 0.f};
#pragma unroll
            for (int i = 0; i < 5; i++) {
                uint32_t d[4] = {sub2(bq[i][0], piv2), 0x3F803F80u, sub2(bq[i][1], piv2), 0x3F803F80u};
                if (i == 4 && four) d[0] = d[2] = 0;
                mma16816((i & 1) ? m1 : m0, d, d[0], d[2]);
            }
            sts64_if((lane & 3) == (lane >> 3), sm + SM_RED + (lane >> 2) * 80 + warp * 8,
                     (lane & 4) ? m0[3] + m1[3] : m0[2] + m1[2], (lane & 4) ? m0[1] + m1[1] : m0[0] + m1[0]);
            cbar();
            const uint32_t ra = sm + SM_RED + (lane >> 2) * 80;
            const float4 p0 = lds128f(ra), p1 = lds128f(ra + 16), p2 = lds128f(ra + 32), p3 = lds128f(ra + 48);
            const float sd = (((p0.x + p0.z) + (p1.x + p1.z)) + ((p2.x + p2.z) + (p3.x + p3.z))) * (1.0f / D_MODEL);
            const float sq = ((p0.y + p0.w) + (p1.y + p1.w)) + ((p2.y + p2.w) + (p3.y + p3.w));
            float mean = bf_hi(piv2) + sd, var = fmaf(sq, 1.0f / D_MODEL, -sd * sd);
            const float mean_o = __shfl_xor_sync(0xffffffffu, mean, 16), var_o = __shfl_xor_sync(0xffffffffu, var, 16);
            uint32_t c1[5][2], sb[5][2];
#pragma unroll
            for (int i = 0; i < 5; i++) {
                c1[i][0] = lds32(sm + SM_CB1 + fo + i * 256); c1[i][1] = lds32(sm + SM_CB1 + fo + i * 256 + 16);
                sb[i][0] = lds32(sm + SM_SB + fo + i * 256); sb[i][1] = lds32(sm + SM_SB + fo + i * 256 + 16);
            }
            const float mean_r = lane < 16 ? mean : mean_o, var_r = lane < 16 ? var : var_o;
            if ((mean_r * mean_r > 16.0f * var_r) == (lane < 16)) { mean = mean_o; var = var_o; }
            const float mean_b = bfr(mean), rden = ln_rden(var);
            const uint32_t mean2 = __byte_perm(__float_as_uint(mean_b), 0, 0x3232);
#pragma unroll
            for (int i = 0; i < 5; i++) {
                bq[i][0] = ln_mod2(bq[i][0], mean2, rden, c1[i][0], sb[i][0]);
                bq[i][1] = ln_mod2(bq[i][1], mean2, rden, c1[i][1], sb[i][1]);
            }
        }
        {
            float c[5][4];
#pragma unroll
            for (int u = 0; u < 5; u++) { c[u][0] = c[u][1] = c[u][2] = c[u][3] = 0.f; }
            if (__builtin_expect(nl < nw, 0)) {
#pragma unroll 1
                for (unsigned it = 0; nl < nw; it++) {
                    gu_more(mbar_test(gbar));
                    if (it > 16 * SPIN_LIMIT) __trap();
                }
            }
#pragma unroll
            for (int i = 0; i < 5; i++) {
                if (i < 4 || !four) {
#pragma unroll
                    for (int u = 0; u < 4; u++) mma16816(c[u], wg[i][u], bq[i][0], bq[i][1]);
                    if (xg) mma16816(c[4], wg[i][4], bq[i][0], bq[i][1]);
                }
            }
            const bool t1 = (lane & 2) != 0;
            const uint32_t rb = sm + SM_GRED + warp * 1280 + ((lane >> 2) * 2 + (lane & 1)) * 16;
#pragma unroll
            for (int u = 0; u < 4; u += 2)
                sts128f(rb + (t1 ? 256 : 0) + u * 256, t1 ? c[u + 1][0] : c[u][0], t1 ? c[u + 1][1] : c[u][1], t1 ? c[u + 1][2] : c[u][2], t1 ? c[u + 1][3] : c[u][3]);
            sts128f(rb + 1024, c[4][0], c[4][1], c[4][2], c[4][3]);
            arrive_if<7>(warp < 5);
        }
        if (__builtin_expect(warp >= 5, 1)) {
            await<7>();
            const int t = tid - 160;
            float4 r = sum8(sm + SM_GRED + min(t, 79) * 16, 1280);
            if ((g & 1) == 0) { r.x = gelu(bfr(r.x)); r.y = gelu(bfr(r.y)); r.z = gelu(bfr(r.z)); r.w = gelu(bfr(r.w)); }
            uint32_t* dst = scr32 + (G_ACT * 4 + (g & 1) * 9216 + (t < 64 ? f0 * 2 + (t >> 4) * 32 : fx * 2) + (t & 15));
            pub32(t < (xg ? 80 : 64), dst, enc(pack_bf(r.x, r.y)));
            pub32(t < (xg ? 80 : 64), dst + 16, enc(pack_bf(r.z, r.w)));
            static_assert(G_Q - G_H <= NCTA * 32, "clear split");
            clr128(t < 32 && G_H + cta * 32 + t < G_Q, scr + (G_H + cta * 32 + t));
            if (warp == 7 && cta < 72) reduce(1);
        } else {
            nl = 0;
            uint4 v[2];
            const int t = min(tid, 143);
            poll<2, 0>(v, scr + (G_ACT + g * 144 + t), 2304, 0,
                                  [&] { if (nl < 6) proj_more(1, mbar_test(proj_bar(1))); });
            put_piece(make_uint4(~mul2(~v[0].x, ~v[1].x), ~mul2(~v[0].y, ~v[1].y), ~mul2(~v[0].z, ~v[1].z), ~mul2(~v[0].w, ~v[1].w)),
                      sm + SM_AVA + t * 4);
            asm volatile("bar.sync 3, 160;" ::: "memory");
            project(1);
        }
    }
    }
}

typedef CUresult (*EncodeFn)(CUtensorMap*, CUtensorMapDataType, cuuint32_t, void*, const cuuint64_t*, const cuuint64_t*,
                             const cuuint32_t*, const cuuint32_t*, CUtensorMapInterleave, CUtensorMapSwizzle,
                             CUtensorMapL2promotion, CUtensorMapFloatOOBfill);

void make3d(EncodeFn fn, CUtensorMap* m, const void* p, uint64_t d0, uint64_t d1, uint64_t d2, uint64_t s1, uint64_t s2,
            uint32_t b0, uint32_t b1, uint32_t b2, CUtensorMapSwizzle sw, CUtensorMapL2promotion promo) {
    cuuint64_t gd[3] = {d0, d1, d2};
    cuuint64_t gs[2] = {s1, s2};
    cuuint32_t bx[3] = {b0, b1, b2};
    cuuint32_t es[3] = {1, 1, 1};
    fn(m, CU_TENSOR_MAP_DATA_TYPE_BFLOAT16, 3, const_cast<void*>(p), gd, gs, bx, es, CU_TENSOR_MAP_INTERLEAVE_NONE, sw, promo,
       CU_TENSOR_MAP_FLOAT_OOB_FILL_NONE);
}

}

extern "C" void kernel_launch(void* const* d_in, const int* in_sizes, int n_in, void* d_out, int out_size) {
    (void)in_sizes; (void)n_in; (void)out_size;
    EncodeFn fn = nullptr;
    cudaDriverEntryPointQueryResult qr;
    cudaGetDriverEntryPoint("cuTensorMapEncodeTiled", (void**)&fn, cudaEnableDefault, &qr);
    cudaFuncSetAttribute(fused_block_kernel, cudaFuncAttributeMaxDynamicSharedMemorySize, SM_TOTAL);
    Params prm;
    const CUtensorMapL2promotion P128 = CU_TENSOR_MAP_L2_PROMOTION_L2_128B, P256 = CU_TENSOR_MAP_L2_PROMOTION_L2_256B;
    make3d(fn, &prm.m[M_K], d_in[1], 64, (uint64_t)NB * 16 * SK, 2, 256, 128, 64, 64, 2, CU_TENSOR_MAP_SWIZZLE_128B, P256);
    make3d(fn, &prm.m[M_V], d_in[2], 64, (uint64_t)NB * 16 * SK, 2, 256, 128, 64, 64, 2, CU_TENSOR_MAP_SWIZZLE_128B, P256);
    make3d(fn, &prm.m[M_WMOD], d_in[10], D_MODEL, D_MODEL, 6, 6 * D_MODEL * 2, D_MODEL * 2, 16, 192, 2, CU_TENSOR_MAP_SWIZZLE_32B, P128);
    make3d(fn, &prm.m[M_WQ], d_in[3], 4096, D_MODEL, 1, 8192, 8192 * D_MODEL, 32, 192, 1, CU_TENSOR_MAP_SWIZZLE_64B, P128);
    for (int x = 0; x < 2; x++) {
        const CUtensorMapSwizzle sp = x ? CU_TENSOR_MAP_SWIZZLE_32B : CU_TENSOR_MAP_SWIZZLE_128B;
        make3d(fn, &prm.m[M_WO + 4 * x], d_in[4], D_MODEL, 4096, 1, D_MODEL * 2, D_MODEL * 2 * 4096, x ? 16 : 64, x ? 128 : 64, 1, sp, P128);
        make3d(fn, &prm.m[M_WD + 4 * x], d_in[8], D_MODEL, FF, 1, D_MODEL * 2, D_MODEL * 2 * FF, x ? 16 : 64, x ? 144 : 48, 1, sp, P128);
        make3d(fn, &prm.m[M_WG + 4 * x], d_in[6], FF, D_MODEL, 1, FF * 2, FF * 2 * D_MODEL, x ? 16 : 64, x ? 192 : 48, 1, sp, P128);
        make3d(fn, &prm.m[M_WU + 4 * x], d_in[7], FF, D_MODEL, 1, FF * 2, FF * 2 * D_MODEL, x ? 16 : 64, x ? 192 : 48, 1, sp, P128);
    }
    void* scr = nullptr;
    void* plan = nullptr;
    cudaGetSymbolAddress(&scr, g_scr);
    cudaGetSymbolAddress(&plan, g_plan);
    cudaLaunchConfig_t cfg = {};
    cfg.gridDim = dim3(NCTA); cfg.blockDim = dim3(NTHREADS); cfg.dynamicSmemBytes = SM_TOTAL; cfg.stream = cudaStreamPerThread;
    cudaLaunchAttribute at[1];
    at[0].id = cudaLaunchAttributeCooperative; at[0].val.cooperative = 1;
    cfg.attrs = at; cfg.numAttrs = 1;
    cudaLaunchKernelEx(&cfg, fused_block_kernel, prm, (const __nv_bfloat16*)d_in[0], (const __nv_bfloat16*)d_in[9],
                       (__nv_bfloat16*)d_out, (uint4*)scr, (const void*)plan);
}
```

```cpp
#include <cuda_runtime.h>
#include <cuda_bf16.h>
#include <cuda.h>
#include <stdint.h>

namespace {

constexpr int D_MODEL = 576;
constexpr int NB = 4;
constexpr int SK = 4096;
constexpr int FF = 4608;
constexpr int NCTA = 128;
constexpr int NTHREADS = 320;
constexpr int NSLOT = 12;
constexpr int TILE_BYTES = 16384;
constexpr int TILES = 32;
constexpr int AV_PITCH = 1168;

constexpr int SM_W0 = 7 * TILE_BYTES;
constexpr int SM_X = 4 * TILE_BYTES;
constexpr int SM_WO = SM_X + 18432;
constexpr int SM_WG = SM_WO + 32768;
constexpr int SM_WD = 0;
constexpr int SM_GRED = 3 * TILE_BYTES;
constexpr int SM_SC = NSLOT * TILE_BYTES;
constexpr int SM_RED = SM_SC + 8192;
constexpr int SM_AVA = SM_RED + 4096;
constexpr int SM_AVB = SM_AVA + 4 * AV_PITCH;
constexpr int SM_CB1 = SM_AVB + 4 * AV_PITCH;
constexpr int SM_SB = SM_CB1 + 4 * AV_PITCH;
constexpr int SM_QS = SM_SB + 4 * AV_PITCH;
constexpr int SM_XR = SM_QS + 128;
constexpr int SM_BAR = SM_XR + 64;
constexpr int CH_KV = 6, CH_WO = 70, CH_GU = 74, CH_WD = 86, CH_X = 92, NCHUNK = 98;
constexpr int REL = NCHUNK, RELW = REL + 64, NBAR = RELW + 2;
constexpr int SM_TAB = SM_BAR + 1312;
static_assert(NBAR * 8 <= 1312, "bars");
constexpr int SM_ADJ = SM_TAB + NCHUNK * 16;
constexpr int SM_ORG = SM_ADJ + 16;
constexpr int SM_TOTAL = SM_ORG + 96;
static_assert(SM_TOTAL <= 232448, "smem");
constexpr int NHARD = 4;

constexpr unsigned SPIN_LIMIT = 1u << 22;
constexpr float LOG2E = 1.4426950408889634f;

enum { M_K = 0, M_V, M_WMOD, M_WQ, M_WO, M_WD, M_WG, M_WU, M_WOX, M_WDX, M_WGX, M_WUX, NMAPS };
struct alignas(16) Plan { uint32_t e[NCHUNK][4]; };
struct Params { CUtensorMap m[NMAPS]; };

constexpr Plan make_plan() {
    Plan pl = {};
    const int paced_from = 13, win_start = 48, win_main = 64;
    const int win_wo = 44, win_gu = 48, win_wd = 32;
    const int slack_main = 32, lag_main = 56, slack_tail = 6, lag_tail = 16;
    const int xkb = 3;
    const unsigned char tail[28] = {70, 92, 71, 93, 72, 73, 74, 75, 94, 76, 77, 78, 79, 95, 80, 81, 82, 83, 96, 97, 84, 85,
                                    86, 87, 88, 89, 90, 91};
    int order[NCHUNK] = {}, kb[NCHUNK] = {}, last_user[NSLOT] = {}, cum = 0;
    for (int p = 0; p < NCHUNK; p++) order[p] = p < 3 ? p : p == 3 ? CH_KV : p <= CH_KV ? p - 1 : p < CH_WO ? p : tail[p - CH_WO];
    for (int i = 0; i < NSLOT; i++) last_user[i] = i >= 9 ? RELW + 1 : i >= 7 ? RELW : 0;
    for (int p = 0; p < NCHUNK; p++) {
        const int c = order[p];
        int map = 0, dst = 0, row = 0, bytes = 0;
        if (c < CH_KV) { map = c < 3 ? M_WMOD : M_WQ; dst = SM_W0 + c * 12288; bytes = 12288; row = (c % 3) * 192; }
        else if (c < CH_WO) { const int i = c - CH_KV; map = i / TILES; dst = (i % NSLOT) * TILE_BYTES; bytes = TILE_BYTES; row = i % TILES; }
        else if (c < CH_GU) { const int t = c - CH_WO; map = M_WO; dst = SM_WO + t * 8192; bytes = 8192; row = t * 64; }
        else if (c < CH_WD) { const int t = c - CH_GU; map = M_WG; dst = SM_WG + t * 6144; bytes = 6144; row = t * 48; }
        else if (c < CH_X) { const int t = c - CH_WD; map = M_WD; dst = SM_WD + t * 6144; bytes = 6144; row = t * 48; }
        else { dst = SM_X; row = c - CH_X; }
        kb[p] = bytes ? bytes / 1024 : xkb;
        cum += kb[p];
        unsigned bar4 = 0;
        if (c >= CH_KV) bar4 = last_user[dst / TILE_BYTES] | (last_user[(dst + (bytes ? bytes : 18432) - 1) / TILE_BYTES] << 8);
        if (c >= CH_KV && c < CH_WO) last_user[dst / TILE_BYTES] = REL + c - CH_KV;
        const bool tl = p >= CH_WO;
        const int win = p < paced_from ? win_start : !tl ? win_main : p < CH_WO + 6 ? win_wo : p < CH_WO + 22 ? win_gu : win_wd;
        const int slack = p < paced_from ? 0 : tl ? slack_tail : slack_main;
        for (int k = 0; k < 2; k++) {
            const int lim = k ? win - slack : win + slack;
            int q = p - 1, sum = kb[p];
            while (q > 0 && (sum + kb[q] <= lim || order[q] >= CH_X)) sum += kb[q--];
            bar4 |= (unsigned)order[q < 0 ? 0 : q] << (16 + 8 * k);
        }
        const int thr = cum - win - (tl ? lag_tail : lag_main);
        pl.e[p][0] = dst | (map << 20) | (c << 24);
        pl.e[p][1] = row | (bytes << 16);
        pl.e[p][2] = (unsigned)(thr < 0 ? 0 : thr) | ((unsigned)cum << 18);
        pl.e[p][3] = bar4;
    }
    return pl;
}
__device__ const Plan g_plan = make_plan();

constexpr int NREP = 4;
constexpr int G_CNT = 0;
constexpr int G_H = G_CNT + 8;
constexpr int G_MOD = G_H + NREP * 288;
constexpr int G_Q = G_MOD + 1152;
constexpr int G_STAT = G_Q + 2048;
constexpr int G_OPART = G_STAT + NCTA * 8;
constexpr int G_X1 = G_OPART + 4 * NCTA * 64;
constexpr int G_ACT = G_X1 + NREP * 288;
constexpr int G_PART = G_ACT + 2 * 2304;
constexpr int G_TOTAL = G_PART + 2 * 72 * 128;
__device__ __align__(128) uint4 g_scr[G_TOTAL];

__device__ __forceinline__ uint32_t enc(uint32_t w) { return max(~w, 1u); }
__device__ __forceinline__ uint32_t encf(float f) { return enc(__float_as_uint(f)); }
__device__ __forceinline__ float decf(uint32_t w) { return __uint_as_float(~w); }
__device__ __forceinline__ float bf_lo(uint32_t w) { return __uint_as_float(w << 16); }
__device__ __forceinline__ float bf_hi(uint32_t w) { return __uint_as_float(w & 0xFFFF0000u); }
__device__ __forceinline__ uint32_t pack_bf(float lo, float hi) {
    uint32_t r;
    asm("cvt.rn.bf16x2.f32 %0, %1, %2;" : "=r"(r) : "f"(hi), "f"(lo));
    return r;
}
__device__ __forceinline__ float bfr(float x) { return __uint_as_float(pack_bf(0.f, x)); }
__device__ __forceinline__ uint32_t mul2(uint32_t a, uint32_t b) { uint32_t r; asm("mul.rn.bf16x2 %0, %1, %2;" : "=r"(r) : "r"(a), "r"(b)); return r; }
__device__ __forceinline__ uint32_t add2(uint32_t a, uint32_t b) { uint32_t r; asm("add.rn.bf16x2 %0, %1, %2;" : "=r"(r) : "r"(a), "r"(b)); return r; }
__device__ __forceinline__ uint32_t sub2(uint32_t a, uint32_t b) { uint32_t r; asm("sub.rn.bf16x2 %0, %1, %2;" : "=r"(r) : "r"(a), "r"(b)); return r; }
__device__ __forceinline__ float ex2(float x) { float r; asm("ex2.approx.ftz.f32 %0, %1;" : "=f"(r) : "f"(x)); return r; }
__device__ __forceinline__ float rcp(float x) { float r; asm("rcp.approx.ftz.f32 %0, %1;" : "=f"(r) : "f"(x)); return r; }
__device__ __forceinline__ float fsqrt(float x) { float r; asm("sqrt.approx.ftz.f32 %0, %1;" : "=f"(r) : "f"(x)); return r; }
__device__ __forceinline__ float sigm(float x) { return rcp(1.0f + ex2(-LOG2E * x)); }
__device__ __forceinline__ float gelu(float g) { return g * sigm(1.5957691216057308f * (g + 0.044715f * g * g * g)); }
__device__ __forceinline__ void mbar_init(uint32_t bar, uint32_t cnt) {
    asm volatile("mbarrier.init.shared::cta.b64 [%0], %1;" ::"r"(bar), "r"(cnt) : "memory");
}
__device__ __forceinline__ void mbar_expect(uint32_t bar, uint32_t bytes) {
    asm volatile("mbarrier.arrive.expect_tx.shared::cta.b64 _, [%0], %1;" ::"r"(bar), "r"(bytes) : "memory");
}
__device__ __forceinline__ void mbar_arrive(uint32_t bar) {
    asm volatile("mbarrier.arrive.shared::cta.b64 _, [%0];" ::"r"(bar) : "memory");
}
__device__ __forceinline__ void mbar_wait(uint32_t bar) {
    asm volatile("{\n.reg .pred p;\n.reg .u32 n;\nmov.u32 n, 0;\n"
                 "W_%=:\nmbarrier.try_wait.parity.shared::cta.b64 p, [%0], 0;\n@p bra D_%=;\n"
                 "add.u32 n, n, 1;\nsetp.lt.u32 p, n, %1;\n@p bra W_%=;\ntrap;\nD_%=:\n}"
                 ::"r"(bar), "n"(SPIN_LIMIT) : "memory");
}
__device__ __forceinline__ bool mbar_test(uint32_t bar) {
    uint32_t ok;
    asm volatile("{\n.reg .pred p;\nmbarrier.test_wait.parity.shared::cta.b64 p, [%1], 0;\nselp.u32 %0, 1, 0, p;\n}" : "=r"(ok) : "r"(bar) : "memory");
    return ok != 0;
}
__device__ __forceinline__ void tma3(uint32_t dst, const CUtensorMap* m, int c0, int c1, int c2, uint32_t bar, uint64_t pol) {
    asm volatile("cp.async.bulk.tensor.3d.shared::cluster.global.mbarrier::complete_tx::bytes.L2::cache_hint [%0], [%1, {%3, %4, %5}], [%2], %6;"
                 ::"r"(dst), "l"(m), "r"(bar), "r"(c0), "r"(c1), "r"(c2), "l"(pol) : "memory");
}
__device__ __forceinline__ void cbar() { asm volatile("bar.sync 1, 256;" ::: "memory"); }
template <int ID>
__device__ __forceinline__ void arrive_if(bool p) {
    asm volatile("{\n.reg .pred q;\nsetp.ne.u32 q, %0, 0;\n@q bar.arrive %1, 256;\n}" ::"r"((uint32_t)p), "n"(ID) : "memory");
}
template <int ID>
__device__ __forceinline__ void await() { asm volatile("bar.sync %0, 256;" ::"n"(ID) : "memory"); }
__device__ __forceinline__ void ldsm4(uint32_t (&r)[4], uint32_t a) {
    asm volatile("ldmatrix.sync.aligned.m8n8.x4.shared.b16 {%0,%1,%2,%3}, [%4];"
                 : "=r"(r[0]), "=r"(r[1]), "=r"(r[2]), "=r"(r[3]) : "r"(a) : "memory");
}
__device__ __forceinline__ void ldsm4t(uint32_t (&r)[4], uint32_t a) {
    asm volatile("ldmatrix.sync.aligned.m8n8.x4.trans.shared.b16 {%0,%1,%2,%3}, [%4];"
                 : "=r"(r[0]), "=r"(r[1]), "=r"(r[2]), "=r"(r[3]) : "r"(a) : "memory");
}
__device__ __forceinline__ void mma16816(float (&c)[4], const uint32_t (&a)[4], uint32_t b0, uint32_t b1) {
    asm volatile("mma.sync.aligned.m16n8k16.row.col.f32.bf16.bf16.f32 {%0,%1,%2,%3}, {%4,%5,%6,%7}, {%8,%9}, {%0,%1,%2,%3};"
                 : "+f"(c[0]), "+f"(c[1]), "+f"(c[2]), "+f"(c[3])
                 : "r"(a[0]), "r"(a[1]), "r"(a[2]), "r"(a[3]), "r"(b0), "r"(b1));
}
__device__ __forceinline__ uint32_t lds32(uint32_t a) {
    uint32_t r; asm volatile("ld.shared.b32 %0, [%1];" : "=r"(r) : "r"(a) : "memory"); return r;
}
__device__ __forceinline__ uint32_t lds16(uint32_t a) {
    unsigned short r; asm volatile("ld.shared.b16 %0, [%1];" : "=h"(r) : "r"(a) : "memory"); return r;
}
__device__ __forceinline__ float ldsf(uint32_t a) { return __uint_as_float(lds32(a)); }
__device__ __forceinline__ uint4 lds128(uint32_t a) {
    uint4 r; asm volatile("ld.shared.v4.b32 {%0,%1,%2,%3}, [%4];" : "=r"(r.x), "=r"(r.y), "=r"(r.z), "=r"(r.w) : "r"(a) : "memory"); return r;
}
__device__ __forceinline__ float4 lds128f(uint32_t a) {
    float4 r; asm volatile("ld.shared.v4.f32 {%0,%1,%2,%3}, [%4];" : "=f"(r.x), "=f"(r.y), "=f"(r.z), "=f"(r.w) : "r"(a) : "memory"); return r;
}
__device__ __forceinline__ void sts16(uint32_t a, uint32_t v) { asm volatile("st.shared.b16 [%0], %1;" ::"r"(a), "h"((unsigned short)v) : "memory"); }
__device__ __forceinline__ void sts32(uint32_t a, uint32_t v) { asm volatile("st.shared.b32 [%0], %1;" ::"r"(a), "r"(v) : "memory"); }
__device__ __forceinline__ void sts64(uint32_t a, uint32_t x, uint32_t y) { asm volatile("st.shared.v2.b32 [%0], {%1,%2};" ::"r"(a), "r"(x), "r"(y) : "memory"); }
__device__ __forceinline__ void sts64_if(bool p, uint32_t a, float x, float y) {
    asm volatile("{\n.reg .pred q;\nsetp.ne.u32 q, %3, 0;\n@q st.shared.v2.f32 [%0], {%1,%2};\n}" ::"r"(a), "f"(x), "f"(y), "r"((uint32_t)p) : "memory");
}
__device__ __forceinline__ void stsf(uint32_t a, float v) { sts32(a, __float_as_uint(v)); }
__device__ __forceinline__ void sts128(uint32_t a, uint4 v) {
    asm volatile("st.shared.v4.b32 [%0], {%1,%2,%3,%4};" ::"r"(a), "r"(v.x), "r"(v.y), "r"(v.z), "r"(v.w) : "memory");
}
__device__ __forceinline__ void sts128f(uint32_t a, float x, float y, float z, float w) {
    asm volatile("st.shared.v4.f32 [%0], {%1,%2,%3,%4};" ::"r"(a), "f"(x), "f"(y), "f"(z), "f"(w) : "memory");
}
__device__ __forceinline__ float4 sum8(uint32_t a, int st) {
    float4 v[8];
#pragma unroll
    for (int w = 0; w < 8; w++) v[w] = lds128f(a + w * st);
#pragma unroll
    for (int o = 4; o; o >>= 1)
#pragma unroll
        for (int w = 0; w < o; w++) { v[w].x += v[w + o].x; v[w].y += v[w + o].y; v[w].z += v[w + o].z; v[w].w += v[w + o].w; }
    return v[0];
}
__device__ __forceinline__ void pub32(bool p, void* a, uint32_t v) {
    asm volatile("{\n.reg .pred q;\nsetp.ne.u32 q, %2, 0;\n@q st.relaxed.gpu.global.b32 [%0], %1;\n}" ::"l"(a), "r"(v), "r"((uint32_t)p) : "memory");
}
__device__ __forceinline__ void pub64(bool p, void* a, uint32_t x, uint32_t y) {
    asm volatile("{\n.reg .pred q;\nsetp.ne.u32 q, %3, 0;\n@q st.relaxed.gpu.global.v2.b32 [%0], {%1,%2};\n}" ::"l"(a), "r"(x), "r"(y), "r"((uint32_t)p) : "memory");
}
__device__ __forceinline__ void st16(bool p, void* a, uint32_t v) {
    asm volatile("{\n.reg .pred q;\nsetp.ne.u32 q, %2, 0;\n@q st.global.b16 [%0], %1;\n}" ::"l"(a), "h"((unsigned short)v), "r"((uint32_t)p) : "memory");
}
__device__ __forceinline__ void clr128(bool p, void* a) {
    asm volatile("{\n.reg .pred q;\nsetp.ne.u32 q, %1, 0;\n@q st.relaxed.gpu.global.v4.b32 [%0], {%2,%2,%2,%2};\n}" ::"l"(a), "r"((uint32_t)p), "r"(0) : "memory");
}
__device__ __forceinline__ uint32_t back32(bool p, const void* a) {
    uint32_t r = 0;
    asm volatile("{\n.reg .pred q;\nsetp.ne.u32 q, %2, 0;\n@q ld.relaxed.gpu.global.b32 %0, [%1];\n}" : "+r"(r) : "l"(a), "r"((uint32_t)p) : "memory");
    return r;
}
__device__ __forceinline__ void ldg_missing(uint4& r, const uint4* p, uint32_t lo) {
    asm volatile("{\n.reg .pred q;\nsetp.eq.u32 q, %5, 0;\n@q ld.relaxed.gpu.global.v4.b32 {%0,%1,%2,%3}, [%4];\n}"
                 : "+r"(r.x), "+r"(r.y), "+r"(r.z), "+r"(r.w) : "l"(p), "r"(lo) : "memory");
}
__device__ __forceinline__ uint32_t min4(const uint4& v) { return min(min(v.x, v.y), min(v.z, v.w)); }
template <int N, int SLEEP, class Side>
__device__ __forceinline__ void poll(uint4 (&v)[N], const uint4* p, int stride, uint32_t skip, Side side) {
    uint32_t lo[N];
#pragma unroll
    for (int i = 0; i < N; i++) { lo[i] = (skip >> i) & 1; v[i] = make_uint4(lo[i], lo[i], lo[i], lo[i]); }
#pragma unroll 1
    for (unsigned it = 0;; it++) {
#pragma unroll
        for (int i = 0; i < N; i++) ldg_missing(v[i], p + i * stride, lo[i]);
        side();
        uint32_t all = 0xFFFFFFFFu;
#pragma unroll
        for (int i = 0; i < N; i++) { lo[i] = min4(v[i]); all = min(all, lo[i]); }
        if (__all_sync(0xffffffffu, all != 0)) break;
        if (it > SPIN_LIMIT) __trap();
        if (SLEEP) __nanosleep(SLEEP);
    }
}
template <int N, int SLEEP>
__device__ __forceinline__ void poll(uint4 (&v)[N], const uint4* p, int stride) { poll<N, SLEEP>(v, p, stride, 0, [] {}); }
__device__ __forceinline__ uint4 unzip(const uint4& e) {
    uint4 r;
    r.x = ~__byte_perm(e.x, e.z, 0x5410);
    r.y = ~__byte_perm(e.x, e.z, 0x7632);
    r.z = ~__byte_perm(e.y, e.w, 0x5410);
    r.w = ~__byte_perm(e.y, e.w, 0x7632);
    return r;
}
__device__ __forceinline__ void put_piece(const uint4& e, uint32_t a) {
    const uint4 u = unzip(e);
    sts32(a, u.x); sts32(a + AV_PITCH, u.y); sts32(a + 2 * AV_PITCH, u.z); sts32(a + 3 * AV_PITCH, u.w);
}
template <int SLEEP, class Side>
__device__ __forceinline__ void gather576(const uint4* src, uint32_t dst, int warp, int tid, Side side) {
    uint4 v[2];
    poll<2, SLEEP>(v, src + tid, 96, warp == 5 ? 0 : 2, side);
    put_piece(v[0], dst + tid * 4);
    if (warp == 5) put_piece(v[1], dst + tid * 4 + 384);
}
__device__ __forceinline__ float ln_rden(float var) { return rcp(bfr(fsqrt(bfr(bfr(fmaxf(var, 0.f)) + 1e-5f)))); }
__device__ __forceinline__ void ln_stats(const uint32_t (&w)[9], float& mean_b, float& rden) {
    const float piv = __shfl_sync(0xffffffffu, bf_lo(w[0]), 0);
    float s = 0.f, q = 0.f;
#pragma unroll
    for (int i = 0; i < 9; i++) {
        const float a = bf_lo(w[i]) - piv, c = bf_hi(w[i]) - piv;
        s += a + c;
        q = fmaf(a, a, fmaf(c, c, q));
    }
#pragma unroll
    for (int o = 16; o; o >>= 1) { s += __shfl_xor_sync(0xffffffffu, s, o); q += __shfl_xor_sync(0xffffffffu, q, o); }
    s *= (1.0f / D_MODEL);
    mean_b = bfr(piv + s);
    rden = ln_rden(fmaf(q, 1.0f / D_MODEL, -s * s));
}
__device__ __forceinline__ float ln_mod(float x, float mean_b, float rden, float scale1, float shift) {
    return bfr(bfr(bfr(x - mean_b) * rden) * scale1) + shift;
}

__device__ __forceinline__ uint32_t ln_mod2(uint32_t x, uint32_t mean2, float rden, uint32_t scale1, uint32_t shift) {
    const uint32_t d = sub2(x, mean2);
    return add2(mul2(pack_bf(bf_lo(d) * rden, bf_hi(d) * rden), scale1), shift);
}

__global__ void __launch_bounds__(NTHREADS, 1)
fused_block_kernel(const __grid_constant__ Params prm, const __nv_bfloat16* __restrict__ x, const __nv_bfloat16* __restrict__ cvec,
                   __nv_bfloat16* __restrict__ out, uint4* __restrict__ scr, const void* __restrict__ plan) {
    extern __shared__ __align__(1024) unsigned char smem_raw[];
    const uint32_t sm = (uint32_t)__cvta_generic_to_shared(smem_raw);
    const uint32_t bars = sm + SM_BAR;
    const int tid = threadIdx.x, cta = blockIdx.x;
    const int g = cta >> 3, j = cta & 7;
    auto kv_row = [&](int n) { return ((n >> 3) * 16 + g) * SK + ((n & 7) * 8 + j) * 64; };
    uint64_t pol;
    asm volatile("createpolicy.fractional.L2::evict_first.b64 %0, 1.0;" : "=l"(pol));
    if (tid == 0) {
        mbar_init(bars + CH_KV * 8, 1);
        asm volatile("fence.mbarrier_init.release.cluster;" ::: "memory");
        mbar_expect(bars + CH_KV * 8, TILE_BYTES);
        tma3(sm, &prm.m[M_K], 0, kv_row(0), 0, bars + CH_KV * 8, pol);
    }
    const int warp = __shfl_sync(0xffffffffu, tid >> 5, 0), lane = tid & 31;
    const int f0 = (g >> 1) * 576 + j * 64, fx = (g >> 1) * 576 + 448 + j * 16;
    const bool xg = j >= 4;

    if (warp == 8) {
        if (lane == 0) {
#pragma unroll
            for (int n = 0; n < 3; n++) mbar_init(bars + n * 8, 1);
            asm volatile("fence.mbarrier_init.release.cluster;" ::: "memory");
#pragma unroll
            for (int n = 0; n < 3; n++) {
                mbar_expect(bars + n * 8, cta < 108 ? 12288 : 0);
                if (cta < 108) tma3(sm + SM_W0 + n * 12288, &prm.m[M_WMOD], (cta % 36) * 16, n * 192, (cta / 36) * 2, bars + n * 8, pol);
            }
#pragma unroll
            for (int n = 3; n < 6 + NHARD; n++) if (n != CH_KV) mbar_init(bars + n * 8, 1);
            asm volatile("fence.mbarrier_init.release.cluster;" ::: "memory");
        }
        __syncwarp();
        asm volatile("bar.arrive 5, %0;" ::"n"(NTHREADS) : "memory");
        asm volatile("bar.sync 4, 96;" ::: "memory");
        if (lane == 0) {
#pragma unroll 1
            for (int n = 0; n < 3; n++) {
                mbar_expect(bars + (3 + n) * 8, 12288);
                mbar_wait(bars + n * 8);
                tma3(sm + SM_W0 + (3 + n) * 12288, &prm.m[M_WQ], cta * 32, n * 192, 0, bars + (3 + n) * 8, pol);
            }
#pragma unroll 1
            for (int n = 1; n < NHARD; n++) {
                mbar_expect(bars + (CH_KV + n) * 8, TILE_BYTES);
                mbar_wait(bars + (n == 1 ? CH_KV : n + 2) * 8);
                tma3(sm + n * TILE_BYTES, &prm.m[M_K], 0, kv_row(n), 0, bars + (CH_KV + n) * 8, pol);
            }
        }
        __syncwarp();
        asm volatile("bar.sync 2, 64;" ::: "memory");
        if (sm & 1023) __trap();
        uint4 e = lds128(sm + SM_TAB + (6 + NHARD) * 16);
#pragma unroll 1
        for (int p = 6 + NHARD; p < NCHUNK; p++) {
            const uint4 nx = lds128(sm + SM_TAB + (p + 1) * 16);
            if (e.x & 0x80000u) {
                const uint32_t tb = bars + ((e.w >> ((lane & 3) * 8)) & 255) * 8;
#pragma unroll 1
                for (unsigned it = 0;; it++) {
                    uint32_t avg;
                    asm volatile("ld.volatile.shared.b32 %0, [%1];" : "=r"(avg) : "r"(sm + SM_ADJ) : "memory");
                    const bool far = avg >= (e.y >> 16);
                    if (__all_sync(0xffffffffu, mbar_test(tb) || ((lane & 3) == 3 && far))) break;
                    if (it > 16 * SPIN_LIMIT) __trap();
                }
                if (lane == 0) {
                    tma3(sm + (e.x & 0x7FFFF), &prm.m[(e.x >> 20) & 15], e.y & 0xFFFF, e.z & 0x3FFFF, 0, bars + (e.x >> 24) * 8, pol);
                }
            }
            e = nx;
        }
        return;
    }
    if (warp == 9) {
        if (lane < NMAPS)
            sts64(sm + SM_ORG + lane * 8,
                  lane <= M_V ? 0 : lane <= M_WQ ? cta * 32 : lane <= M_WD ? j * 64 : lane <= M_WU ? f0 : lane <= M_WDX ? 512 + j * 16 : fx,
                  (lane & 2) ? 0 : (lane & 1) ? g * 288 : g * 256);
        if (lane == 0) sts32(sm + SM_ADJ, 0);
        uint4 pe[4];
#pragma unroll
        for (int i = 0; i < 4; i++) pe[i] = __ldg(reinterpret_cast<const uint4*>(plan) + min(lane + 32 * i, NCHUNK - 1));
        if (lane == 0) {
#pragma unroll
            for (int n = 6 + NHARD; n < NBAR; n++) mbar_init(bars + n * 8, n >= REL && n < RELW ? 2 : 1);
            asm volatile("fence.mbarrier_init.release.cluster;" ::: "memory");
        }
        __syncwarp();
        asm volatile("bar.arrive 5, %0;" ::"n"(NTHREADS) : "memory");
        asm volatile("bar.sync 4, 96;" ::: "memory");
#pragma unroll
        for (int i = 0; i < 4; i++) {
            if ((pe[i].y >> 16) == 0) {
                const uint32_t t = pe[i].y, h = t & 1;
                pe[i].x += xg ? (t - 2) * 6144 + (M_WGX << 20) : t < 2 ? h * 4096 + (M_WOX << 20) : 8192 + h * 4608 + (M_WDX << 20);
                pe[i].y = xg ? (t - 2 < 3 ? (t - 2) * 192 + (6144 << 16) : 0)
                             : t < 2 ? h * 128 + (4096 << 16) : t >= 4 ? h * 144 + (4608 << 16) : 0;
            }
            if (((pe[i].x >> 20) & 3) == 2 && (pe[i].x >> 24) >= CH_WO) pe[i].x += (g & 1) << 20;
            const int p = lane + 32 * i;
            if (p < NCHUNK) {
                const uint32_t org = sm + SM_ORG + ((pe[i].x >> 20) & 15) * 8;
                if (p >= 6 + NHARD) mbar_expect(bars + (pe[i].x >> 24) * 8, pe[i].y >> 16);
                const uint32_t c1 = ((pe[i].x >> 20) & 15) <= M_V ? kv_row(pe[i].y & 0xFFFF) : lds32(org + 4) + (pe[i].y & 0xFFFF);
                sts128(sm + SM_TAB + p * 16, make_uint4(pe[i].x | ((pe[i].y >> 16) ? 0x80000u : 0u), lds32(org) | (pe[i].z << 16),
                                                        c1 | (pe[i].z & 0xFFFC0000u), pe[i].w));
            }
        }
        asm volatile("bar.arrive 2, 64;" ::: "memory");
        __syncwarp();
        if (lane < NMAPS) asm volatile("prefetch.tensormap [%0];" ::"l"(&prm.m[lane]) : "memory");
        if (lane == 0) {
            int n = 0;
            uint32_t kb = 0;
#pragma unroll 1
            for (unsigned it = 0; n < NCHUNK; it++) {
                while (n < NCHUNK && mbar_test(bars + (lds32(sm + SM_TAB + n * 16) >> 24) * 8)) n++;
                const uint32_t now = n == NCHUNK ? 2048 : n ? lds32(sm + SM_TAB + n * 16 - 8) >> 18 : 0;
                const uint32_t all = now == kb ? back32(true, scr + G_CNT) : atomicAdd(reinterpret_cast<unsigned*>(scr + G_CNT), now - kb);
                asm volatile("st.volatile.shared.b32 [%0], %1;" ::"r"(sm + SM_ADJ), "r"(all / NCTA) : "memory");
                pub32(all + now - kb == NCTA * 2048, scr + G_CNT, 0);
                kb = now;
                if (it > SPIN_LIMIT) __trap();
            }
        }
        return;
    }

    if (warp == 0) asm volatile("bar.arrive 4, 96;" ::: "memory");
    uint2 cw[3];
    uint32_t xw[9];
#pragma unroll
    for (int i = 0; i < 3; i++) cw[i] = cta < 108 ? __ldg(reinterpret_cast<const uint2*>(cvec) + min(tid + 256 * i, 575)) : make_uint2(0, 0);
#pragma unroll
    for (int i = 0; i < 9; i++) xw[i] = cta < 36 && warp >= 4 ? __ldg(reinterpret_cast<const uint32_t*>(x) + (warp & 3) * 288 + lane + 32 * i) : 0u;
    clr128(cta < 32 && tid < 64, scr + (G_Q + cta * 64 + tid));
    uint32_t cleared = back32(cta < 32 && tid < 64, scr + (G_Q + cta * 64 + tid));
    const int mi = lane >> 3, r8 = lane & 7;
    const uint32_t bfrag = ((lane >> 2) & 3) * AV_PITCH + (lane & 3) * 4;
    uint32_t* const scr32 = reinterpret_cast<uint32_t*>(scr);
    uint2* const scr64 = reinterpret_cast<uint2*>(scr);
    const int pr = warp >> 1, hf = warp & 1;

#pragma unroll
    for (int i = 0; i < 3; i++) {
        const int p = min(tid + 256 * i, 575);
        const float a0 = bf_lo(cw[i].x), a1 = bf_hi(cw[i].x), a2 = bf_lo(cw[i].y), a3 = bf_hi(cw[i].y);
        sts64(sm + SM_AVA + (p / 144) * AV_PITCH + (p % 144) * 8, pack_bf(a0 * sigm(a0), a1 * sigm(a1)), pack_bf(a2 * sigm(a2), a3 * sigm(a3)));
    }
    if (cta < 36 && warp >= 4) {
        float mean_b, rden;
        ln_stats(xw, mean_b, rden);
        if (lane == 0) sts64(sm + SM_QS + (warp & 3) * 8, __float_as_uint(mean_b), __float_as_uint(rden));
#pragma unroll
        for (int i = 0; i < 9; i++) sts32(sm + SM_CB1 + (warp & 3) * 1152 + (lane + 32 * i) * 4, xw[i]);
    }
    if (cleared) __trap();
    uint32_t mod_lo = 0, mod_hi = 0;
#pragma unroll 1
    for (int it = 0; it < 2; it++) {
        if (it == 1) gather576<300>(scr + (G_H + (g % NREP) * 288), sm + SM_AVB, warp, tid, [] {});
        if (it) cbar(); else asm volatile("bar.sync 5, %0;" ::"n"(NTHREADS) : "memory");
        if (cta < 108 || it == 1) {
            const int k = (mi >> 1) * 8 + r8;
            const uint32_t base = sm + SM_W0 + (it ? 36864 + k * 64 : (mi & 1) * 6144 + k * 32);
            const uint32_t ch = it ? (((mi & 1) * 2) ^ (r8 >> 1)) : (r8 >> 2);
            const uint32_t a0 = base + (ch << 4), a1 = base + ((ch ^ 1) << 4), kb = it ? 1024 : 512;
            const uint32_t bb = sm + (it ? SM_AVB : SM_AVA) + bfrag + warp * 32;
            float c0[4] = {0.f, 0.f, 0.f, 0.f}, c1[4] = {0.f, 0.f, 0.f, 0.f};
            uint32_t bq[5][2];
#pragma unroll
            for (int i = 0; i < 5; i++) { bq[i][0] = lds32(bb + i * 256); bq[i][1] = lds32(bb + i * 256 + 16); }
            if (warp >= 4) bq[4][0] = bq[4][1] = 0;
#pragma unroll
            for (int i = 0; i < 3; i++) mbar_wait(bars + (it * 3 + i) * 8);
#pragma unroll
            for (int i = 0; i < 5; i++) {
                const int ks = min(warp + 8 * i, 35);
                const int cq = ks / 12;
                const uint32_t off = cq * 12288 + (ks - cq * 12) * kb;
                uint32_t u[4], v[4];
                ldsm4t(u, a0 + off);
                ldsm4t(v, a1 + off);
                mma16816(c0, u, bq[i][0], bq[i][1]);
                mma16816(c1, v, bq[i][0], bq[i][1]);
            }
            const bool t1 = (lane & 2) != 0;
            sts128f(sm + SM_RED + warp * 512 + (t1 ? 256 : 0) + ((lane >> 2) * 2 + (lane & 1)) * 16,
                    t1 ? c1[0] : c0[0], t1 ? c1[1] : c0[1], t1 ? c1[2] : c0[2], t1 ? c1[3] : c0[3]);
            cbar();
            if (warp == 7) {
                const float4 r = sum8(sm + SM_RED + lane * 16, 512);
                if (it == 0 && cta < 36) {
                    const uint32_t xp = sm + SM_CB1 + (lane & 1) * 2304 + (cta * 16 + (lane >> 1)) * 2;
                    const float4 st = lds128f(sm + SM_QS + (lane & 1) * 16);
                    const float h0 = ln_mod(bf_lo(lds16(xp)), st.x, st.y, bfr(1.0f + bfr(r.z)), bfr(r.x));
                    const float h1 = ln_mod(bf_lo(lds16(xp + 1152)), st.z, st.w, bfr(1.0f + bfr(r.w)), bfr(r.y));
                    const uint32_t hv = enc(pack_bf(h0, h1));
#pragma unroll
                    for (int i = 0; i < NREP; i++) pub32(true, scr32 + (G_H * 4 + i * 1152 + cta * 32 + lane), hv);
                } else {
                    const uint32_t lo = enc(pack_bf(r.x, r.y)), hi = enc(pack_bf(r.z, r.w));
                    pub32(it, scr32 + (G_Q * 4 + cta * 64 + lane), lo);
                    pub32(it, scr32 + (G_Q * 4 + cta * 64 + 32 + lane), hi);
                    if (it == 0) { mod_lo = lo; mod_hi = hi; }
                }
            }
        }
        if (tid == 192) mbar_arrive(bars + (RELW + it) * 8);
    }

    {
        constexpr int PER = (G_TOTAL - G_STAT + 71) / 72;
        static_assert(PER <= 1024, "clear split");
        const int i = G_STAT + max(cta - 36, 0) * PER + tid, end = cta < 36 ? 0 : min(i - tid + PER, G_TOTAL);
#pragma unroll
        for (int k = 0; k < 1024; k += 256) clr128(i + k < end, scr + i + k);
#pragma unroll
        for (int k = 0; k < 1024; k += 256) cleared |= back32(i + k < end, scr + i + k);
    }
    if (tid < 128) {
        uint4 v[1];
        poll<1, 40>(v, scr + (G_Q + g * 128 + tid), 0);
        put_piece(v[0], sm + SM_AVA + tid * 4);
    }
    if (cleared) __trap();
    cbar();
    if (warp == 7) {
        uint32_t* dst = scr32 + (G_MOD * 4 + ((cta / 72) * 1152 + (cta % 36) * 16) * 2 + lane);
        pub32(cta >= 36 && cta < 108, dst, mod_lo);
        pub32(cta >= 36 && cta < 108, dst + 1152, mod_hi);
    }
    {
        auto fetch_mod = [&]() {
            if (warp < 5) {
                const int t = min(tid, 143);
                uint4 v[4];
                poll<4, 40>(v, scr + (G_MOD + 288 + t), 144);
#pragma unroll
                for (int i = 0; i < 4; i++) {
                    uint4 u = unzip(v[i]);
                    if (i >= 2) {
                        u.x = pack_bf(1.0f + bf_lo(u.x), 1.0f + bf_hi(u.x)); u.y = pack_bf(1.0f + bf_lo(u.y), 1.0f + bf_hi(u.y));
                        u.z = pack_bf(1.0f + bf_lo(u.z), 1.0f + bf_hi(u.z)); u.w = pack_bf(1.0f + bf_lo(u.w), 1.0f + bf_hi(u.w));
                    }
                    const uint32_t d = sm + (i >= 2 ? SM_CB1 : SM_SB) + (t + 144 * (i & 1)) * 4;
                    sts32(d, u.x); sts32(d + AV_PITCH, u.y); sts32(d + 2 * AV_PITCH, u.z); sts32(d + 3 * AV_PITCH, u.w);
                }
            } else if (warp == 7 && cta < 72) {
                sts16(sm + SM_XR + (lane & 7) * 8 + (lane >> 3) * 2,
                      reinterpret_cast<const unsigned short*>(x)[(lane >> 3) * D_MODEL + cta * 8 + (lane & 7)]);
                uint4 v[2];
                poll<2, 40>(v, scr + (G_MOD + cta * 4 + ((lane & 7) >> 1)), 864);
                sts128(sm + SM_QS + (lane & 7) * 16, make_uint4(~((lane & 1) ? v[0].z : v[0].x), ~((lane & 1) ? v[0].w : v[0].y),
                                                                ~((lane & 1) ? v[1].z : v[1].x), ~((lane & 1) ? v[1].w : v[1].y)));
            }
        };
        const uint32_t koff = (hf * 32 + (mi & 1) * 8 + r8) * 128;
        uint32_t sw[4];
#pragma unroll
        for (int c = 0; c < 4; c++) sw[c] = koff + (((2 * c + (mi >> 1)) ^ r8) << 4);
#pragma unroll 1
        for (int i = pr; i < TILES; i += 4) {
            uint32_t qf[8][2];
#pragma unroll
            for (int ks = 0; ks < 8; ks++) {
                const uint32_t a = sm + SM_AVA + (i >> 3) * AV_PITCH + ((lane >> 2) & 1) * 256 + ks * 32 + (lane & 3) * 4;
                qf[ks][0] = lds32(a); qf[ks][1] = lds32(a + 16);
            }
            mbar_wait(bars + (CH_KV + i) * 8);
            const uint32_t tb = sm + (i % NSLOT) * TILE_BYTES;
            float c[4][4];
#pragma unroll
            for (int u = 0; u < 4; u++) { c[u][0] = c[u][1] = c[u][2] = c[u][3] = 0.f; }
#pragma unroll
            for (int ks = 0; ks < 4; ks++) {
#pragma unroll
                for (int u = 0; u < 4; u++) {
                    uint32_t a[4];
                    ldsm4(a, tb + (u >> 1) * 8192 + (u & 1) * 2048 + sw[ks]);
                    mma16816(c[u], a, qf[(u >> 1) * 4 + ks][0], qf[(u >> 1) * 4 + ks][1]);
                }
            }
            __syncwarp();
            if (lane == 0) mbar_arrive(bars + (REL + i) * 8);
            const bool t1 = (lane & 2) != 0, hi = (lane & 1) != 0;
            const float p0 = t1 ? (hi ? c[1][2] + c[3][2] : c[1][0] + c[3][0]) : (hi ? c[0][2] + c[2][2] : c[0][0] + c[2][0]);
            const float p1 = t1 ? (hi ? c[1][3] + c[3][3] : c[1][1] + c[3][1]) : (hi ? c[0][3] + c[2][3] : c[0][1] + c[2][1]);
            const uint32_t w = pack_bf(bfr(p0) * 0.08838834764831845f, bfr(p1) * 0.08838834764831845f);
            const uint32_t a = sm + SM_SC + (i * 64 + hf * 32 + (lane & 3) * 8 + (lane >> 2)) * 2;
            sts16(a, w & 0xFFFFu);
            sts16(a + 4096, w >> 16);
            if ((i >> 2) == 4 + cta % 3) fetch_mod();
        }
    }
    cbar();

    {
        const uint32_t a = sm + SM_SC + tid * 32;
        const uint4 u0 = lds128(a), u1 = lds128(a + 16);
        const uint32_t w[8] = {u0.x, u0.y, u0.z, u0.w, u1.x, u1.y, u1.z, u1.w};
        float e[16], m = -INFINITY;
#pragma unroll
        for (int i = 0; i < 8; i++) { e[2 * i] = bf_lo(w[i]); e[2 * i + 1] = bf_hi(w[i]); m = fmaxf(m, fmaxf(e[2 * i], e[2 * i + 1])); }
#pragma unroll
        for (int o = 16; o; o >>= 1) m = fmaxf(m, __shfl_xor_sync(0xffffffffu, m, o));
        float l = 0.f;
#pragma unroll
        for (int i = 0; i < 16; i++) { e[i] = ex2((e[i] - m) * LOG2E); l += e[i]; }
#pragma unroll
        for (int o = 16; o; o >>= 1) l += __shfl_xor_sync(0xffffffffu, l, o);
        if (lane == 0) sts64(sm + SM_RED + warp * 8, encf(m), encf(l));
        cbar();
        if (warp == 0) {
            pub32(lane < 16, scr32 + (G_STAT * 4 + cta * 32 + lane), lds32(sm + SM_RED + (lane & 15) * 4));
            uint4 v[1];
            poll<1, 40>(v, scr + (G_STAT + (g * 8 + (lane >> 2)) * 8 + (lane & 3)), 0);
            const float ma = decf(v[0].x), mb = decf(v[0].z);
            float ga = ma, gb = mb;
#pragma unroll
            for (int o = 4; o < 32; o <<= 1) { ga = fmaxf(ga, __shfl_xor_sync(0xffffffffu, ga, o)); gb = fmaxf(gb, __shfl_xor_sync(0xffffffffu, gb, o)); }
            float la = decf(v[0].y) * ex2((ma - ga) * LOG2E), lb = decf(v[0].w) * ex2((mb - gb) * LOG2E);
#pragma unroll
            for (int o = 4; o < 32; o <<= 1) { la += __shfl_xor_sync(0xffffffffu, la, o); lb += __shfl_xor_sync(0xffffffffu, lb, o); }
            sts128f(sm + SM_RED + 64 + (lane & 3) * 16, ga, rcp(la), gb, rcp(lb));
        }
        cbar();
        const float f = ex2((m - ldsf(sm + SM_RED + 64 + warp * 8)) * LOG2E) * ldsf(sm + SM_RED + 68 + warp * 8);
        uint4 o0, o1;
        o0.x = pack_bf(e[0] * f, e[1] * f); o0.y = pack_bf(e[2] * f, e[3] * f); o0.z = pack_bf(e[4] * f, e[5] * f); o0.w = pack_bf(e[6] * f, e[7] * f);
        o1.x = pack_bf(e[8] * f, e[9] * f); o1.y = pack_bf(e[10] * f, e[11] * f); o1.z = pack_bf(e[12] * f, e[13] * f); o1.w = pack_bf(e[14] * f, e[15] * f);
        sts128(a, o0); sts128(a + 16, o1);
        cbar();
    }

    uint32_t wa[2][18][4];
    const bool pw = warp < 4 || (warp == 4 && j < 4);
    const uint32_t astep = warp < 4 ? 2048 : 512;
    const uint32_t aoff = warp < 4 ? ((mi >> 1) * 8 + r8) * 128 + (((warp * 2 + (mi & 1)) ^ r8) << 4)
                                   : ((mi >> 1) * 8 + r8) * 32 + (((mi & 1) ^ (r8 >> 2)) << 4);
    const uint32_t abase[2] = {sm + (warp < 4 ? SM_WO : SM_X) + aoff, sm + (warp < 4 ? SM_WD : SM_X + 8192) + aoff};
    int nl = 0;
    auto proj_bar = [&](int rd) {
        const int c = min(lane, 3 + 2 * rd);
        return bars + (warp < 4 ? (rd ? CH_WD : CH_WO) + c : CH_X + 4 * rd + c / (2 + rd)) * 8;
    };
    auto proj_more = [&](int rd, bool t) {
        const int nr = min(__ffs(~__ballot_sync(0xffffffffu, t) | 0x100) - 1, 4 + 2 * rd);
        if (nr > nl) {
#pragma unroll
            for (int c = 0; c < 4 + 2 * rd; c++) {
                if (c >= nl && c < nr) {
#pragma unroll
                    for (int u = c * (4 - rd); u < (c + 1) * (4 - rd); u++) ldsm4t(wa[rd][u], abase[rd] + u * astep);
                }
            }
            nl = nr;
        }
    };
    {
        float o[4][4];
#pragma unroll
        for (int u = 0; u < 4; u++) { o[u][0] = o[u][1] = o[u][2] = o[u][3] = 0.f; }
        const uint32_t voff = hf * 8192 + ((mi >> 1) * 8 + r8) * 128;
        uint32_t sw[4];
#pragma unroll
        for (int u = 0; u < 4; u++) sw[u] = voff + (((2 * u + (mi & 1)) ^ r8) << 4);
        const uint32_t pb = sm + SM_SC + ((lane >> 2) & 1) * 4096 + (lane & 3) * 4 - TILES * 128;
        auto v_tile = [&](int i) {
            uint32_t pf[4][2];
#pragma unroll
            for (int kk = 0; kk < 4; kk++) { pf[kk][0] = lds32(pb + i * 128 + kk * 32); pf[kk][1] = lds32(pb + i * 128 + kk * 32 + 16); }
            const uint32_t tb = sm + (i % NSLOT) * TILE_BYTES;
            mbar_wait(bars + (CH_KV + i) * 8);
#pragma unroll
            for (int kk = 0; kk < 4; kk++) {
#pragma unroll
                for (int u = 0; u < 4; u++) {
                    uint32_t a[4];
                    ldsm4t(a, tb + kk * 2048 + sw[u]);
                    mma16816(o[u], a, pf[kk][0], pf[kk][1]);
                }
            }
            __syncwarp();
            if (lane == 0) mbar_arrive(bars + (REL + i) * 8);
        };
#pragma unroll 1
        for (int t = 0; t <= 8; t++) {
            const int gb = t == 8 ? 3 : (t & 1) ? (t - 3) >> 1 : -1;
            bool todo = t < 8;
            uint4 v[2];
            poll<2, 0>(v, scr + (G_OPART + (gb * NCTA + g * 8 + (lane & 3) * 2) * 64 + (tid >> 2)), 64, gb < 0 ? 3 : 0, [&] {
                if (todo) {
                    v_tile(TILES + pr + 4 * t);
                    if (t & 1) {
                        const int u = lane & 3;
                        const uint32_t red = sm + ((t & 2) ? SM_RED : SM_AVB);
                        const uint32_t a = red + pr * 1024 + (hf * 64 + u * 16 + (lane >> 2)) * 4;
                        float w[4];
#pragma unroll
                        for (int q = 0; q < 4; q++) w[q] = u == 0 ? o[0][q] : u == 1 ? o[1][q] : u == 2 ? o[2][q] : o[3][q];
                        stsf(a, w[0]); stsf(a + 512, w[1]); stsf(a + 32, w[2]); stsf(a + 512 + 32, w[3]);
#pragma unroll
                        for (int q = 0; q < 4; q++) { o[q][0] = o[q][1] = o[q][2] = o[q][3] = 0.f; }
                        cbar();
                        const uint32_t r = red + tid * 4;
                        pub32(true, scr32 + (G_OPART * 4 + ((t >> 1) * NCTA + cta) * 256 + tid),
                              encf((ldsf(r) + ldsf(r + 1024)) + (ldsf(r + 2048) + ldsf(r + 3072))));
                    }
                } else if (warp < 5 && nl < 4) {
                    proj_more(0, mbar_test(proj_bar(0)));
                }
                todo = false;
            });
            if (gb >= 0) {
                const bool od = lane & 1;
                const float s0 = decf(v[0].x) + decf(v[1].x), s1 = decf(v[0].y) + decf(v[1].y);
                const float s2 = decf(v[0].z) + decf(v[1].z), s3 = decf(v[0].w) + decf(v[1].w);
                float a0 = (od ? s2 : s0) + __shfl_xor_sync(0xffffffffu, od ? s0 : s2, 1);
                float a1 = (od ? s3 : s1) + __shfl_xor_sync(0xffffffffu, od ? s1 : s3, 1);
                a0 += __shfl_xor_sync(0xffffffffu, a0, 2);
                a1 += __shfl_xor_sync(0xffffffffu, a1, 2);
                sts32(sm + SM_AVA + gb * AV_PITCH + (tid >> 2) * 8 + (lane & 1) * 4, pack_bf(a0, a1));
            }
        }
    }

    auto project = [&](int rd) {
        uint32_t b4[9][4];
#pragma unroll
        for (int u = 0; u < 8 + rd; u++) ldsm4(b4[u], sm + SM_AVA + (r8 & 3) * AV_PITCH + mi * 16 + u * 64);
        if (__builtin_expect(nl < 4 + 2 * rd, 0)) {
#pragma unroll 1
            for (unsigned it = 0; nl < 4 + 2 * rd; it++) {
                proj_more(rd, mbar_test(proj_bar(rd)));
                if (it > 16 * SPIN_LIMIT) __trap();
            }
        }
        float c[4][4];
#pragma unroll
        for (int u = 0; u < 4; u++) { c[u][0] = c[u][1] = c[u][2] = c[u][3] = 0.f; }
#pragma unroll
        for (int u = 0; u < 16 + 2 * rd; u++) mma16816(c[u & 3], wa[rd][u], b4[u >> 1][(u & 1) * 2], b4[u >> 1][(u & 1) * 2 + 1]);
        const bool hi = (lane & 2) != 0;
        const int ob = (warp < 4 ? j * 8 + warp * 2 : 64 + j * 2) + (hi ? 1 : 0);
        pub64(pw, scr64 + ((G_PART + rd * 72 * 128 + (ob * 16 + g) * 8) * 2 + (lane >> 2) * 2 + (lane & 1)),
              encf(hi ? (c[2][2] + c[3][2]) + (c[0][2] + c[1][2]) : (c[2][0] + c[3][0]) + (c[0][0] + c[1][0])),
              encf(hi ? (c[2][3] + c[3][3]) + (c[0][3] + c[1][3]) : (c[2][1] + c[3][1]) + (c[0][1] + c[1][1])));
    };
    auto reduce = [&](int rd) {
        const uint32_t g01 = lds32(sm + SM_QS + (lane & 7) * 16 + rd * 8), g23 = lds32(sm + SM_QS + (lane & 7) * 16 + rd * 8 + 4);
        const uint32_t r01 = lds32(sm + SM_XR + (lane & 7) * 8), r23 = lds32(sm + SM_XR + 4 + (lane & 7) * 8);
        uint4 w[4];
        poll<4, 0>(w, scr + (G_PART + rd * 72 * 128 + cta * 128 + lane), 32);
        float t[4] = {(decf(w[0].x) + decf(w[1].x)) + (decf(w[2].x) + decf(w[3].x)), (decf(w[0].y) + decf(w[1].y)) + (decf(w[2].y) + decf(w[3].y)),
                      (decf(w[0].z) + decf(w[1].z)) + (decf(w[2].z) + decf(w[3].z)), (decf(w[0].w) + decf(w[1].w)) + (decf(w[2].w) + decf(w[3].w))};
#pragma unroll
        for (int q = 0; q < 4; q++) t[q] += __shfl_xor_sync(0xffffffffu, t[q], 8);
#pragma unroll
        for (int q = 0; q < 4; q++) t[q] += __shfl_xor_sync(0xffffffffu, t[q], 16);
        const uint32_t x01 = add2(r01, mul2(g01, pack_bf(t[0], t[1]))), x23 = add2(r23, mul2(g23, pack_bf(t[2], t[3])));
        if (rd == 1) {
            const uint32_t ov = (lane & 16) ? x23 : x01;
            st16(true, out + ((lane >> 3) * D_MODEL + cta * 8 + (lane & 7)), (lane & 8) ? ov >> 16 : ov);
        } else {
#pragma unroll
            for (int i = 0; i < NREP; i += 4)
                pub64(true, scr64 + (G_X1 * 2 + (i + (lane >> 3)) * 576 + cta * 8 + (lane & 7)), enc(x01), enc(x23));
            sts64(sm + SM_XR + (lane & 7) * 8, x01, x23);
        }
    };
    arrive_if<6>(warp >= 5);
    if (__builtin_expect(warp < 5, 1)) {
        await<6>();
        project(0);
    } else if (warp == 7 && cta < 72) {
        reduce(0);
    }
    {
        uint32_t wg[5][5][4];
        const bool four = warp >= 4;
        uint32_t gbar;
        {
            const int ks = min(warp + 8 * (lane >> 1), 35);
            gbar = bars + ((xg && (lane & 1)) ? CH_X + 2 + ks / 12 : CH_GU + ks / 3) * 8;
        }
        const int nw = four ? 4 : 5;
        auto gu_more = [&](bool t) {
            const int nr = min((__ffs(~__ballot_sync(0xffffffffu, t) | 0x400) - 1) >> 1, nw);
            if (nr > nl) {
#pragma unroll
                for (int i = 0; i < 5; i++) {
                    const int k = (warp + 8 * i) * 16 + (mi >> 1) * 8 + r8;
                    const uint32_t ag = sm + SM_WG + k * 128;
                    if (i >= nl && i < nr) {
#pragma unroll
                        for (int u = 0; u < 4; u++) ldsm4t(wg[i][u], ag + (((2 * u + (mi & 1)) ^ r8) << 4));
                        if (xg) ldsm4t(wg[i][4], sm + SM_X + k * 32 + (((mi & 1) ^ (r8 >> 2)) << 4));
                    }
                }
                nl = nr;
            }
        };
        nl = 0;
        gather576<0>(scr + (G_X1 + (g % NREP) * 288), sm + SM_AVB, warp, tid, [&] { if (nl < nw) gu_more(mbar_test(gbar)); });
        cbar();
        uint32_t bq[5][2];
        {
            const uint32_t fo = bfrag + warp * 32;
#pragma unroll
            for (int i = 0; i < 5; i++) { bq[i][0] = lds32(sm + SM_AVB + fo + i * 256); bq[i][1] = lds32(sm + SM_AVB + fo + i * 256 + 16); }
            const uint32_t piv2 = lane < 16 ? 0u : __byte_perm(lds32(sm + SM_AVB + ((lane >> 2) & 3) * AV_PITCH), 0, 0x1010);
            float m0[4] = {0.f, 0.f, 0.f, 0.f}, m1[4] = {0.f, 0.f, 0.f, 0.f};
#pragma unroll
            for (int i = 0; i < 5; i++) {
                uint32_t d[4] = {sub2(bq[i][0], piv2), 0x3F803F80u, sub2(bq[i][1], piv2), 0x3F803F80u};
                if (i == 4 && four) d[0] = d[2] = 0;
                mma16816((i & 1) ? m1 : m0, d, d[0], d[2]);
            }
            sts64_if((lane & 3) == (lane >> 3), sm + SM_RED + (lane >> 2) * 80 + warp * 8,
                     (lane & 4) ? m0[3] + m1[3] : m0[2] + m1[2], (lane & 4) ? m0[1] + m1[1] : m0[0] + m1[0]);
            cbar();
            const uint32_t ra = sm + SM_RED + (lane >> 2) * 80;
            const float4 p0 = lds128f(ra), p1 = lds128f(ra + 16), p2 = lds128f(ra + 32), p3 = lds128f(ra + 48);
            const float sd = (((p0.x + p0.z) + (p1.x + p1.z)) + ((p2.x + p2.z) + (p3.x + p3.z))) * (1.0f / D_MODEL);
            const float sq = ((p0.y + p0.w) + (p1.y + p1.w)) + ((p2.y + p2.w) + (p3.y + p3.w));
            float mean = bf_hi(piv2) + sd, var = fmaf(sq, 1.0f / D_MODEL, -sd * sd);
            const float mean_o = __shfl_xor_sync(0xffffffffu, mean, 16), var_o = __shfl_xor_sync(0xffffffffu, var, 16);
            uint32_t c1[5][2], sb[5][2];
#pragma unroll
            for (int i = 0; i < 5; i++) {
                c1[i][0] = lds32(sm + SM_CB1 + fo + i * 256); c1[i][1] = lds32(sm + SM_CB1 + fo + i * 256 + 16);
                sb[i][0] = lds32(sm + SM_SB + fo + i * 256); sb[i][1] = lds32(sm + SM_SB + fo + i * 256 + 16);
            }
            const float mean_r = lane < 16 ? mean : mean_o, var_r = lane < 16 ? var : var_o;
            if ((mean_r * mean_r > 16.0f * var_r) == (lane < 16)) { mean = mean_o; var = var_o; }
            const float mean_b = bfr(mean), rden = ln_rden(var);
            const uint32_t mean2 = __byte_perm(__float_as_uint(mean_b), 0, 0x3232);
#pragma unroll
            for (int i = 0; i < 5; i++) {
                bq[i][0] = ln_mod2(bq[i][0], mean2, rden, c1[i][0], sb[i][0]);
                bq[i][1] = ln_mod2(bq[i][1], mean2, rden, c1[i][1], sb[i][1]);
            }
        }
        {
            float c[5][4];
#pragma unroll
            for (int u = 0; u < 5; u++) { c[u][0] = c[u][1] = c[u][2] = c[u][3] = 0.f; }
            if (__builtin_expect(nl < nw, 0)) {
#pragma unroll 1
                for (unsigned it = 0; nl < nw; it++) {
                    gu_more(mbar_test(gbar));
                    if (it > 16 * SPIN_LIMIT) __trap();
                }
            }
#pragma unroll
            for (int i = 0; i < 5; i++) {
                if (i < 4 || !four) {
#pragma unroll
                    for (int u = 0; u < 4; u++) mma16816(c[u], wg[i][u], bq[i][0], bq[i][1]);
                    if (xg) mma16816(c[4], wg[i][4], bq[i][0], bq[i][1]);
                }
            }
            const bool t1 = (lane & 2) != 0;
            const uint32_t rb = sm + SM_GRED + warp * 1280 + ((lane >> 2) * 2 + (lane & 1)) * 16;
#pragma unroll
            for (int u = 0; u < 4; u += 2)
                sts128f(rb + (t1 ? 256 : 0) + u * 256, t1 ? c[u + 1][0] : c[u][0], t1 ? c[u + 1][1] : c[u][1], t1 ? c[u + 1][2] : c[u][2], t1 ? c[u + 1][3] : c[u][3]);
            sts128f(rb + 1024, c[4][0], c[4][1], c[4][2], c[4][3]);
            arrive_if<7>(warp < 5);
        }
        if (__builtin_expect(warp >= 5, 1)) {
            await<7>();
            const int t = tid - 160;
            float4 r = sum8(sm + SM_GRED + min(t, 79) * 16, 1280);
            if ((g & 1) == 0) { r.x = gelu(bfr(r.x)); r.y = gelu(bfr(r.y)); r.z = gelu(bfr(r.z)); r.w = gelu(bfr(r.w)); }
            uint32_t* dst = scr32 + (G_ACT * 4 + (g & 1) * 9216 + (t < 64 ? f0 * 2 + (t >> 4) * 32 : fx * 2) + (t & 15));
            pub32(t < (xg ? 80 : 64), dst, enc(pack_bf(r.x, r.y)));
            pub32(t < (xg ? 80 : 64), dst + 16, enc(pack_bf(r.z, r.w)));
            static_assert(G_Q - G_H <= NCTA * 32, "clear split");
            clr128(t < 32 && G_H + cta * 32 + t < G_Q, scr + (G_H + cta * 32 + t));
            if (warp == 7 && cta < 72) reduce(1);
        } else {
            nl = 0;
            uint4 v[2];
            const int t = min(tid, 143);
            poll<2, 0>(v, scr + (G_ACT + g * 144 + t), 2304, 0,
                                  [&] { if (nl < 6) proj_more(1, mbar_test(proj_bar(1))); });
            put_piece(make_uint4(~mul2(~v[0].x, ~v[1].x), ~mul2(~v[0].y, ~v[1].y), ~mul2(~v[0].z, ~v[1].z), ~mul2(~v[0].w, ~v[1].w)),
                      sm + SM_AVA + t * 4);
            asm volatile("bar.sync 3, 160;" ::: "memory");
            project(1);
        }
    }
}

typedef CUresult (*EncodeFn)(CUtensorMap*, CUtensorMapDataType, cuuint32_t, void*, const cuuint64_t*, const cuuint64_t*,
                             const cuuint32_t*, const cuuint32_t*, CUtensorMapInterleave, CUtensorMapSwizzle,
                             CUtensorMapL2promotion, CUtensorMapFloatOOBfill);

void make3d(EncodeFn fn, CUtensorMap* m, const void* p, uint64_t d0, uint64_t d1, uint64_t d2, uint64_t s1, uint64_t s2,
            uint32_t b0, uint32_t b1, uint32_t b2, CUtensorMapSwizzle sw, CUtensorMapL2promotion promo) {
    cuuint64_t gd[3] = {d0, d1, d2};
    cuuint64_t gs[2] = {s1, s2};
    cuuint32_t bx[3] = {b0, b1, b2};
    cuuint32_t es[3] = {1, 1, 1};
    fn(m, CU_TENSOR_MAP_DATA_TYPE_BFLOAT16, 3, const_cast<void*>(p), gd, gs, bx, es, CU_TENSOR_MAP_INTERLEAVE_NONE, sw, promo,
       CU_TENSOR_MAP_FLOAT_OOB_FILL_NONE);
}

}

extern "C" void kernel_launch(void* const* d_in, const int* in_sizes, int n_in, void* d_out, int out_size) {
    (void)in_sizes; (void)n_in; (void)out_size;
    EncodeFn fn = nullptr;
    cudaDriverEntryPointQueryResult qr;
    cudaGetDriverEntryPoint("cuTensorMapEncodeTiled", (void**)&fn, cudaEnableDefault, &qr);
    cudaFuncSetAttribute(fused_block_kernel, cudaFuncAttributeMaxDynamicSharedMemorySize, SM_TOTAL);
    Params prm;
    const CUtensorMapL2promotion P128 = CU_TENSOR_MAP_L2_PROMOTION_L2_128B, P256 = CU_TENSOR_MAP_L2_PROMOTION_L2_256B;
    make3d(fn, &prm.m[M_K], d_in[1], 64, (uint64_t)NB * 16 * SK, 2, 256, 128, 64, 64, 2, CU_TENSOR_MAP_SWIZZLE_128B, P256);
    make3d(fn, &prm.m[M_V], d_in[2], 64, (uint64_t)NB * 16 * SK, 2, 256, 128, 64, 64, 2, CU_TENSOR_MAP_SWIZZLE_128B, P256);
    make3d(fn, &prm.m[M_WMOD], d_in[10], D_MODEL, D_MODEL, 6, 6 * D_MODEL * 2, D_MODEL * 2, 16, 192, 2, CU_TENSOR_MAP_SWIZZLE_32B, P128);
    make3d(fn, &prm.m[M_WQ], d_in[3], 4096, D_MODEL, 1, 8192, 8192 * D_MODEL, 32, 192, 1, CU_TENSOR_MAP_SWIZZLE_64B, P128);
    for (int x = 0; x < 2; x++) {
        const CUtensorMapSwizzle sp = x ? CU_TENSOR_MAP_SWIZZLE_32B : CU_TENSOR_MAP_SWIZZLE_128B;
        make3d(fn, &prm.m[M_WO + 4 * x], d_in[4], D_MODEL, 4096, 1, D_MODEL * 2, D_MODEL * 2 * 4096, x ? 16 : 64, x ? 128 : 64, 1, sp, P128);
        make3d(fn, &prm.m[M_WD + 4 * x], d_in[8], D_MODEL, FF, 1, D_MODEL * 2, D_MODEL * 2 * FF, x ? 16 : 64, x ? 144 : 48, 1, sp, P128);
        make3d(fn, &prm.m[M_WG + 4 * x], d_in[6], FF, D_MODEL, 1, FF * 2, FF * 2 * D_MODEL, x ? 16 : 64, x ? 192 : 48, 1, sp, P128);
        make3d(fn, &prm.m[M_WU + 4 * x], d_in[7], FF, D_MODEL, 1, FF * 2, FF * 2 * D_MODEL, x ? 16 : 64, x ? 192 : 48, 1, sp, P128);
    }
    void* scr = nullptr;
    void* plan = nullptr;
    cudaGetSymbolAddress(&scr, g_scr);
    cudaGetSymbolAddress(&plan, g_plan);
    cudaLaunchConfig_t cfg = {};
    cfg.gridDim = dim3(NCTA); cfg.blockDim = dim3(NTHREADS); cfg.dynamicSmemBytes = SM_TOTAL; cfg.stream = cudaStreamPerThread;
    cudaLaunchAttribute at[1];
    at[0].id = cudaLaunchAttributeCooperative; at[0].val.cooperative = 1;
    cfg.attrs = at; cfg.numAttrs = 1;
    cudaLaunchKernelEx(&cfg, fused_block_kernel, prm, (const __nv_bfloat16*)d_in[0], (const __nv_bfloat16*)d_in[9],
                       (__nv_bfloat16*)d_out, (uint4*)scr, (const void*)plan);
}
```

```cpp
#include <cuda_runtime.h>
#include <cuda_bf16.h>
#include <cuda.h>
#include <stdint.h>

namespace {

constexpr int D_MODEL = 576;
constexpr int NB = 4;
constexpr int SK = 4096;
constexpr int FF = 4608;
constexpr int NCTA = 128;
constexpr int NTHREADS = 384;
constexpr int NSLOT = 12;
constexpr int TILE_BYTES = 16384;
constexpr int TILES = 32;
constexpr int AV_PITCH = 1168;

constexpr int SM_W0 = 7 * TILE_BYTES;
constexpr int SM_X = 4 * TILE_BYTES;
constexpr int SM_WO = SM_X + 18432;
constexpr int SM_WG = SM_WO + 32768;
constexpr int SM_WD = 0;
constexpr int SM_GRED = 3 * TILE_BYTES;
constexpr int SM_SC = NSLOT * TILE_BYTES;
constexpr int SM_RED = SM_SC + 8192;
constexpr int SM_AVA = SM_RED + 4096;
constexpr int SM_AVB = SM_AVA + 4 * AV_PITCH;
constexpr int SM_CB1 = SM_AVB + 4 * AV_PITCH;
constexpr int SM_SB = SM_CB1 + 4 * AV_PITCH;
constexpr int SM_QS = SM_SB + 4 * AV_PITCH;
constexpr int SM_XR = SM_QS + 128;
constexpr int SM_BAR = SM_XR + 64;
constexpr int CH_KV = 6, CH_WO = 70, CH_GU = 74, CH_WD = 86, CH_X = 92, NCHUNK = 98;
constexpr int REL = NCHUNK, RELW = REL + 64, NBAR = RELW + 2;
constexpr int SM_TAB = SM_BAR + 1312;
static_assert(NBAR * 8 <= 1312, "bars");
constexpr int SM_ADJ = SM_TAB + NCHUNK * 16;
constexpr int SM_ORG = SM_ADJ + 16;
constexpr int SM_MODW = SM_ORG + 96;
constexpr int SM_RACE = SM_MODW + 256;
constexpr int SM_TOTAL = SM_RACE + 32;
static_assert(SM_TOTAL <= 232448, "smem");
constexpr int NFIRST = 2;
constexpr int NHARD = 4;

constexpr unsigned SPIN_LIMIT = 1u << 22;
constexpr float LOG2E = 1.4426950408889634f;

enum { M_K = 0, M_V, M_WMOD, M_WQ, M_WO, M_WD, M_WG, M_WU, M_WOX, M_WDX, M_WGX, M_WUX, NMAPS };
struct alignas(16) Plan { uint32_t e[NCHUNK][4]; };
struct Params { CUtensorMap m[NMAPS]; };

constexpr Plan make_plan() {
    Plan pl = {};
    const int paced_from = 11, win_start = 64, win_main = 64;
    const int win_wo = 60, win_gu = 60, win_wd = 44;
    const int slack_main = 32, lag_main = 20, slack_tail = 12, lag_tail = 12;
    const int xkb = 3;
    const unsigned char tail[28] = {70, 92, 71, 93, 72, 73, 74, 75, 94, 76, 77, 78, 79, 95, 80, 81, 82, 83, 96, 97, 84, 85,
                                    86, 87, 88, 89, 90, 91};
    int order[NCHUNK] = {}, kb[NCHUNK] = {}, last_user[NSLOT] = {}, cum = 0;
    for (int p = 0; p < NCHUNK; p++) order[p] = p < NFIRST ? CH_KV + p : p < CH_KV + NFIRST ? p - NFIRST : p < CH_WO ? p : tail[p - CH_WO];
    for (int i = 0; i < NSLOT; i++) last_user[i] = i >= 9 ? RELW + 1 : i >= 7 ? RELW : 0;
    for (int p = 0; p < NCHUNK; p++) {
        const int c = order[p];
        int map = 0, dst = 0, row = 0, bytes = 0;
        if (c < CH_KV) { map = c < 3 ? M_WMOD : M_WQ; dst = SM_W0 + c * 12288; bytes = 12288; row = (c % 3) * 192; }
        else if (c < CH_WO) { const int i = c - CH_KV; map = i / TILES; dst = (i % NSLOT) * TILE_BYTES; bytes = TILE_BYTES; row = i % TILES; }
        else if (c < CH_GU) { const int t = c - CH_WO; map = M_WO; dst = SM_WO + t * 8192; bytes = 8192; row = t * 64; }
        else if (c < CH_WD) { const int t = c - CH_GU; map = M_WG; dst = SM_WG + t * 6144; bytes = 6144; row = t * 48; }
        else if (c < CH_X) { const int t = c - CH_WD; map = M_WD; dst = SM_WD + t * 6144; bytes = 6144; row = t * 48; }
        else { dst = SM_X; row = c - CH_X; }
        kb[p] = bytes ? bytes / 1024 : xkb;
        cum += kb[p];
        unsigned bar4 = 0;
        if (c >= CH_KV) bar4 = last_user[dst / TILE_BYTES] | (last_user[(dst + (bytes ? bytes : 18432) - 1) / TILE_BYTES] << 8);
        if (c >= CH_KV && c < CH_WO) last_user[dst / TILE_BYTES] = REL + c - CH_KV;
        const bool tl = p >= CH_WO;
        const int win = p < paced_from ? win_start : !tl ? win_main : p < CH_WO + 6 ? win_wo : p < CH_WO + 22 ? win_gu : win_wd;
        const int slack = p < paced_from ? 0 : tl ? slack_tail : slack_main;
        for (int k = 0; k < 2; k++) {
            const int lim = k ? win - slack : win + slack;
            int q = p - 1, sum = kb[p];
            while (q > 0 && (sum + kb[q] <= lim || order[q] >= CH_X)) sum += kb[q--];
            bar4 |= (unsigned)order[q < 0 ? 0 : q] << (16 + 8 * k);
        }
        const int thr = cum - win - (tl ? lag_tail : lag_main);
        pl.e[p][0] = dst | (map << 20) | (c << 24);
        pl.e[p][1] = row | (bytes << 16);
        pl.e[p][2] = (unsigned)(thr < 0 ? 0 : thr) | ((unsigned)cum << 18);
        pl.e[p][3] = bar4;
    }
    return pl;
}
__device__ const Plan g_plan = make_plan();

constexpr int SLOT = 512;
constexpr int G_CNT = 0;
constexpr int G_H = SLOT;
constexpr int G_MOD = G_H + 4 * SLOT;
constexpr int G_UNIT = G_MOD + 1152;
constexpr int G_Q = G_MOD + 3 * SLOT;
constexpr int G_STAT = G_Q + 8 * SLOT;
constexpr int G_OPART = G_STAT + 4 * SLOT;
constexpr int G_O3 = G_OPART + 3 * NCTA * 64;
constexpr int G_ACT = G_O3 + 32 * SLOT;
constexpr int G_X1 = G_ACT + 18 * SLOT;
constexpr int G_PART = G_X1 + 4 * SLOT;
constexpr int G_PROBE = G_PART + 72 * SLOT;
constexpr int G_TOTAL = G_PROBE + 16 * SLOT;
static_assert(G_TOTAL * 16 <= (2 << 20), "one page");
__device__ __align__(128) uint4 g_scr[(4 << 20) / 16];
__host__ __device__ constexpr int home(int i) { return ((i >> 8) ^ (i >> 9) ^ (i >> 12) ^ (i >> 13) ^ (i >> 15)) & 1; }
__device__ __forceinline__ int unit_on(int slot, int side) { return slot + ((home(slot) ^ side) << 8); }

__device__ __forceinline__ uint32_t enc(uint32_t w) { return max(~w, 1u); }
__device__ __forceinline__ uint32_t encf(float f) { return enc(__float_as_uint(f)); }
__device__ __forceinline__ float decf(uint32_t w) { return __uint_as_float(~w); }
__device__ __forceinline__ float bf_lo(uint32_t w) { return __uint_as_float(w << 16); }
__device__ __forceinline__ float bf_hi(uint32_t w) { return __uint_as_float(w & 0xFFFF0000u); }
__device__ __forceinline__ uint32_t pack_bf(float lo, float hi) {
    uint32_t r;
    asm("cvt.rn.bf16x2.f32 %0, %1, %2;" : "=r"(r) : "f"(hi), "f"(lo));
    return r;
}
__device__ __forceinline__ float bfr(float x) { return __uint_as_float(pack_bf(0.f, x)); }
__device__ __forceinline__ uint32_t mul2(uint32_t a, uint32_t b) { uint32_t r; asm("mul.rn.bf16x2 %0, %1, %2;" : "=r"(r) : "r"(a), "r"(b)); return r; }
__device__ __forceinline__ uint32_t add2(uint32_t a, uint32_t b) { uint32_t r; asm("add.rn.bf16x2 %0, %1, %2;" : "=r"(r) : "r"(a), "r"(b)); return r; }
__device__ __forceinline__ uint32_t sub2(uint32_t a, uint32_t b) { uint32_t r; asm("sub.rn.bf16x2 %0, %1, %2;" : "=r"(r) : "r"(a), "r"(b)); return r; }
__device__ __forceinline__ float ex2(float x) { float r; asm("ex2.approx.ftz.f32 %0, %1;" : "=f"(r) : "f"(x)); return r; }
__device__ __forceinline__ float rcp(float x) { float r; asm("rcp.approx.ftz.f32 %0, %1;" : "=f"(r) : "f"(x)); return r; }
__device__ __forceinline__ float fsqrt(float x) { float r; asm("sqrt.approx.ftz.f32 %0, %1;" : "=f"(r) : "f"(x)); return r; }
__device__ __forceinline__ float sigm(float x) { return rcp(1.0f + ex2(-LOG2E * x)); }
__device__ __forceinline__ float gelu(float g) { return g * sigm(1.5957691216057308f * (g + 0.044715f * g * g * g)); }
__device__ __forceinline__ void mbar_init(uint32_t bar, uint32_t cnt) {
    asm volatile("mbarrier.init.shared::cta.b64 [%0], %1;" ::"r"(bar), "r"(cnt) : "memory");
}
__device__ __forceinline__ void mbar_expect(uint32_t bar, uint32_t bytes) {
    asm volatile("mbarrier.arrive.expect_tx.shared::cta.b64 _, [%0], %1;" ::"r"(bar), "r"(bytes) : "memory");
}
__device__ __forceinline__ void mbar_arrive(uint32_t bar) {
    asm volatile("mbarrier.arrive.shared::cta.b64 _, [%0];" ::"r"(bar) : "memory");
}
__device__ __forceinline__ void mbar_wait(uint32_t bar) {
    asm volatile("{\n.reg .pred p;\n.reg .u32 n;\nmov.u32 n, 0;\n"
                 "W_%=:\nmbarrier.try_wait.parity.shared::cta.b64 p, [%0], 0;\n@p bra D_%=;\n"
                 "add.u32 n, n, 1;\nsetp.lt.u32 p, n, %1;\n@p bra W_%=;\ntrap;\nD_%=:\n}"
                 ::"r"(bar), "n"(SPIN_LIMIT) : "memory");
}
__device__ __forceinline__ bool mbar_test(uint32_t bar) {
    uint32_t ok;
    asm volatile("{\n.reg .pred p;\nmbarrier.test_wait.parity.shared::cta.b64 p, [%1], 0;\nselp.u32 %0, 1, 0, p;\n}" : "=r"(ok) : "r"(bar) : "memory");
    return ok != 0;
}
__device__ __forceinline__ void tma3(uint32_t dst, const CUtensorMap* m, int c0, int c1, int c2, uint32_t bar, uint64_t pol) {
    asm volatile("cp.async.bulk.tensor.3d.shared::cluster.global.mbarrier::complete_tx::bytes.L2::cache_hint [%0], [%1, {%3, %4, %5}], [%2], %6;"
                 ::"r"(dst), "l"(m), "r"(bar), "r"(c0), "r"(c1), "r"(c2), "l"(pol) : "memory");
}
__device__ __forceinline__ void cbar() { asm volatile("bar.sync 1, 256;" ::: "memory"); }
template <int ID>
__device__ __forceinline__ void arrive_if(bool p) {
    asm volatile("{\n.reg .pred q;\nsetp.ne.u32 q, %0, 0;\n@q bar.arrive %1, 256;\n}" ::"r"((uint32_t)p), "n"(ID) : "memory");
}
template <int ID>
__device__ __forceinline__ void await() { asm volatile("bar.sync %0, 256;" ::"n"(ID) : "memory"); }
__device__ __forceinline__ void ldsm4(uint32_t (&r)[4], uint32_t a) {
    asm volatile("ldmatrix.sync.aligned.m8n8.x4.shared.b16 {%0,%1,%2,%3}, [%4];"
                 : "=r"(r[0]), "=r"(r[1]), "=r"(r[2]), "=r"(r[3]) : "r"(a) : "memory");
}
__device__ __forceinline__ void ldsm4t(uint32_t (&r)[4], uint32_t a) {
    asm volatile("ldmatrix.sync.aligned.m8n8.x4.trans.shared.b16 {%0,%1,%2,%3}, [%4];"
                 : "=r"(r[0]), "=r"(r[1]), "=r"(r[2]), "=r"(r[3]) : "r"(a) : "memory");
}
__device__ __forceinline__ void mma16816(float (&c)[4], const uint32_t (&a)[4], uint32_t b0, uint32_t b1) {
    asm volatile("mma.sync.aligned.m16n8k16.row.col.f32.bf16.bf16.f32 {%0,%1,%2,%3}, {%4,%5,%6,%7}, {%8,%9}, {%0,%1,%2,%3};"
                 : "+f"(c[0]), "+f"(c[1]), "+f"(c[2]), "+f"(c[3])
                 : "r"(a[0]), "r"(a[1]), "r"(a[2]), "r"(a[3]), "r"(b0), "r"(b1));
}
__device__ __forceinline__ uint32_t lds32(uint32_t a) {
    uint32_t r; asm volatile("ld.shared.b32 %0, [%1];" : "=r"(r) : "r"(a) : "memory"); return r;
}
__device__ __forceinline__ uint32_t lds16(uint32_t a) {
    unsigned short r; asm volatile("ld.shared.b16 %0, [%1];" : "=h"(r) : "r"(a) : "memory"); return r;
}
__device__ __forceinline__ float ldsf(uint32_t a) { return __uint_as_float(lds32(a)); }
__device__ __forceinline__ uint4 lds128(uint32_t a) {
    uint4 r; asm volatile("ld.shared.v4.b32 {%0,%1,%2,%3}, [%4];" : "=r"(r.x), "=r"(r.y), "=r"(r.z), "=r"(r.w) : "r"(a) : "memory"); return r;
}
__device__ __forceinline__ float4 lds128f(uint32_t a) {
    float4 r; asm volatile("ld.shared.v4.f32 {%0,%1,%2,%3}, [%4];" : "=f"(r.x), "=f"(r.y), "=f"(r.z), "=f"(r.w) : "r"(a) : "memory"); return r;
}
__device__ __forceinline__ void sts16(uint32_t a, uint32_t v) { asm volatile("st.shared.b16 [%0], %1;" ::"r"(a), "h"((unsigned short)v) : "memory"); }
__device__ __forceinline__ void sts32(uint32_t a, uint32_t v) { asm volatile("st.shared.b32 [%0], %1;" ::"r"(a), "r"(v) : "memory"); }
__device__ __forceinline__ void sts64(uint32_t a, uint32_t x, uint32_t y) { asm volatile("st.shared.v2.b32 [%0], {%1,%2};" ::"r"(a), "r"(x), "r"(y) : "memory"); }
__device__ __forceinline__ void sts64_if(bool p, uint32_t a, float x, float y) {
    asm volatile("{\n.reg .pred q;\nsetp.ne.u32 q, %3, 0;\n@q st.shared.v2.f32 [%0], {%1,%2};\n}" ::"r"(a), "f"(x), "f"(y), "r"((uint32_t)p) : "memory");
}
__device__ __forceinline__ void stsf(uint32_t a, float v) { sts32(a, __float_as_uint(v)); }
__device__ __forceinline__ void sts128(uint32_t a, uint4 v) {
    asm volatile("st.shared.v4.b32 [%0], {%1,%2,%3,%4};" ::"r"(a), "r"(v.x), "r"(v.y), "r"(v.z), "r"(v.w) : "memory");
}
__device__ __forceinline__ void sts128f(uint32_t a, float x, float y, float z, float w) {
    asm volatile("st.shared.v4.f32 [%0], {%1,%2,%3,%4};" ::"r"(a), "f"(x), "f"(y), "f"(z), "f"(w) : "memory");
}
__device__ __forceinline__ int near_side(uint32_t sm) {
    const uint4 a = lds128(sm + SM_RACE), b = lds128(sm + SM_RACE + 16);
    const int ta = min(min(0, (int)(a.y - a.x)), min((int)(a.z - a.x), (int)(a.w - a.x)));
    const int tb = min(min((int)(b.x - a.x), (int)(b.y - a.x)), min((int)(b.z - a.x), (int)(b.w - a.x)));
    return tb < ta;
}
__device__ __forceinline__ float4 sum8(uint32_t a, int st) {
    float4 v[8];
#pragma unroll
    for (int w = 0; w < 8; w++) v[w] = lds128f(a + w * st);
#pragma unroll
    for (int o = 4; o; o >>= 1)
#pragma unroll
        for (int w = 0; w < o; w++) { v[w].x += v[w + o].x; v[w].y += v[w + o].y; v[w].z += v[w + o].z; v[w].w += v[w + o].w; }
    return v[0];
}
__device__ __forceinline__ void pub32(bool p, void* a, uint32_t v) {
    asm volatile("{\n.reg .pred q;\nsetp.ne.u32 q, %2, 0;\n@q st.relaxed.gpu.global.b32 [%0], %1;\n}" ::"l"(a), "r"(v), "r"((uint32_t)p) : "memory");
}
__device__ __forceinline__ void pub64(bool p, void* a, uint32_t x, uint32_t y) {
    asm volatile("{\n.reg .pred q;\nsetp.ne.u32 q, %3, 0;\n@q st.relaxed.gpu.global.v2.b32 [%0], {%1,%2};\n}" ::"l"(a), "r"(x), "r"(y), "r"((uint32_t)p) : "memory");
}
__device__ __forceinline__ void st16(bool p, void* a, uint32_t v) {
    asm volatile("{\n.reg .pred q;\nsetp.ne.u32 q, %2, 0;\n@q st.global.b16 [%0], %1;\n}" ::"l"(a), "h"((unsigned short)v), "r"((uint32_t)p) : "memory");
}
__device__ __forceinline__ void clr128(bool p, void* a) {
    asm volatile("{\n.reg .pred q;\nsetp.ne.u32 q, %1, 0;\n@q st.relaxed.gpu.global.v4.b32 [%0], {%2,%2,%2,%2};\n}" ::"l"(a), "r"((uint32_t)p), "r"(0) : "memory");
}
__device__ __forceinline__ uint32_t back32(bool p, const void* a) {
    uint32_t r = 0;
    asm volatile("{\n.reg .pred q;\nsetp.ne.u32 q, %2, 0;\n@q ld.relaxed.gpu.global.b32 %0, [%1];\n}" : "+r"(r) : "l"(a), "r"((uint32_t)p) : "memory");
    return r;
}
__device__ __forceinline__ uint32_t settle(bool p, void* a) {
    uint32_t r = 0;
    asm volatile("{\n.reg .pred q;\nsetp.ne.u32 q, %2, 0;\n@q atom.relaxed.gpu.global.exch.b32 %0, [%1], 0;\n}" : "+r"(r) : "l"(a), "r"((uint32_t)p) : "memory");
    return r;
}
__device__ __forceinline__ void ldg_missing(uint4& r, const uint4* p, uint32_t lo) {
    asm volatile("{\n.reg .pred q;\nsetp.eq.u32 q, %5, 0;\n@q ld.relaxed.gpu.global.v4.b32 {%0,%1,%2,%3}, [%4];\n}"
                 : "+r"(r.x), "+r"(r.y), "+r"(r.z), "+r"(r.w) : "l"(p), "r"(lo) : "memory");
}
__device__ __forceinline__ uint32_t min4(const uint4& v) { return min(min(v.x, v.y), min(v.z, v.w)); }
template <int N, int SLEEP, class Side>
__device__ __forceinline__ void poll(uint4 (&v)[N], const uint4* p, int stride, uint32_t skip, Side side) {
    uint32_t lo[N];
#pragma unroll
    for (int i = 0; i < N; i++) { lo[i] = (skip >> i) & 1; v[i] = make_uint4(lo[i], lo[i], lo[i], lo[i]); }
#pragma unroll 1
    for (unsigned it = 0;; it++) {
#pragma unroll
        for (int i = 0; i < N; i++) ldg_missing(v[i], p + i * stride, lo[i]);
        if (it > SPIN_LIMIT) __trap();
        side();
        uint32_t all = 0xFFFFFFFFu;
#pragma unroll
        for (int i = 0; i < N; i++) { lo[i] = min4(v[i]); all = min(all, lo[i]); }
        if (__all_sync(0xffffffffu, all != 0)) break;
        if (SLEEP) __nanosleep(SLEEP);
    }
}
template <int N, class More>
__device__ __forceinline__ void poll_test(uint4 (&v)[N], const uint4* p, int stride, uint32_t skip, uint32_t bar, More more) {
    uint32_t lo[N];
#pragma unroll
    for (int i = 0; i < N; i++) { lo[i] = (skip >> i) & 1; v[i] = make_uint4(lo[i], lo[i], lo[i], lo[i]); }
#pragma unroll
    for (int i = 0; i < N; i++) ldg_missing(v[i], p + i * stride, lo[i]);
#pragma unroll 1
    for (unsigned it = 0;; it++) {
        const bool t = mbar_test(bar);
        uint32_t all = 0xFFFFFFFFu;
#pragma unroll
        for (int i = 0; i < N; i++) { lo[i] = min4(v[i]); all = min(all, lo[i]); }
        if (__all_sync(0xffffffffu, all != 0)) break;
#pragma unroll
        for (int i = 0; i < N; i++) ldg_missing(v[i], p + i * stride, lo[i]);
        more(t);
        if (it > SPIN_LIMIT) __trap();
    }
}
template <int N, int SLEEP>
__device__ __forceinline__ void poll(uint4 (&v)[N], const uint4* p, int stride) { poll<N, SLEEP>(v, p, stride, 0, [] {}); }
__device__ __forceinline__ uint4 unzip(const uint4& e) {
    uint4 r;
    r.x = ~__byte_perm(e.x, e.z, 0x5410);
    r.y = ~__byte_perm(e.x, e.z, 0x7632);
    r.z = ~__byte_perm(e.y, e.w, 0x5410);
    r.w = ~__byte_perm(e.y, e.w, 0x7632);
    return r;
}
__device__ __forceinline__ void put_piece(const uint4& e, uint32_t a) {
    const uint4 u = unzip(e);
    sts32(a, u.x); sts32(a + AV_PITCH, u.y); sts32(a + 2 * AV_PITCH, u.z); sts32(a + 3 * AV_PITCH, u.w);
}
__device__ __forceinline__ void put576(const uint4 (&v)[2], uint32_t dst, int warp, int tid) {
    put_piece(v[0], dst + tid * 4);
    if (warp == 5) put_piece(v[1], dst + tid * 4 + 384);
}
__device__ __forceinline__ float ln_rden(float var) { return rcp(bfr(fsqrt(bfr(bfr(fmaxf(var, 0.f)) + 1e-5f)))); }
__device__ __forceinline__ void ln_stats(const uint32_t (&w)[9], float& mean_b, float& rden) {
    const float piv = __shfl_sync(0xffffffffu, bf_lo(w[0]), 0);
    float s = 0.f, q = 0.f;
#pragma unroll
    for (int i = 0; i < 9; i++) {
        const float a = bf_lo(w[i]) - piv, c = bf_hi(w[i]) - piv;
        s += a + c;
        q = fmaf(a, a, fmaf(c, c, q));
    }
#pragma unroll
    for (int o = 16; o; o >>= 1) { s += __shfl_xor_sync(0xffffffffu, s, o); q += __shfl_xor_sync(0xffffffffu, q, o); }
    s *= (1.0f / D_MODEL);
    mean_b = bfr(piv + s);
    rden = ln_rden(fmaf(q, 1.0f / D_MODEL, -s * s));
}
__device__ __forceinline__ float ln_mod(float x, float mean_b, float rden, float scale1, float shift) {
    return bfr(bfr(bfr(x - mean_b) * rden) * scale1) + shift;
}

__device__ __forceinline__ uint32_t ln_mod2(uint32_t x, uint32_t mean2, float rden, uint32_t scale1, uint32_t shift) {
    const uint32_t d = sub2(x, mean2);
    return add2(mul2(pack_bf(bf_lo(d) * rden, bf_hi(d) * rden), scale1), shift);
}

__global__ void __launch_bounds__(NTHREADS, 1)
fused_block_kernel(const __nv_bfloat16* __restrict__ x, const __nv_bfloat16* __restrict__ cvec, __nv_bfloat16* __restrict__ out,
                   uint4* __restrict__ scr, const void* __restrict__ plan, const __grid_constant__ Params prm) {
    extern __shared__ __align__(1024) unsigned char smem_raw[];
    const uint32_t sm = (uint32_t)__cvta_generic_to_shared(smem_raw);
    const uint32_t bars = sm + SM_BAR;
    const int tid = threadIdx.x, cta = blockIdx.x;
    const int g = cta >> 3, j = cta & 7;
    const int jt = (j & 1) * 3 ^ ((j >> 1) & 1) * 9 ^ (j >> 2) * 33;
    auto kv_row = [&](int n) { return ((n >> 3) * 16 + g) * SK + (jt ^ (n & 5) ^ (n & 2) * 8) * 64; };
    uint64_t pol;
    asm volatile("createpolicy.fractional.L2::evict_first.b64 %0, 1.0;" : "=l"(pol));
    if (tid == 0) {
#pragma unroll
        for (int n = 0; n < NFIRST; n++) mbar_init(bars + (CH_KV + n) * 8, 1);
        asm volatile("fence.mbarrier_init.release.cluster;" ::: "memory");
#pragma unroll
        for (int n = 0; n < NFIRST; n++) {
            mbar_expect(bars + (CH_KV + n) * 8, TILE_BYTES);
            tma3(sm + n * TILE_BYTES, &prm.m[M_K], 0, kv_row(n), 0, bars + (CH_KV + n) * 8, pol);
        }
    }
    if (tid < 32) asm volatile("bar.arrive 4, 96;" ::: "memory");
    if (tid < 256) {
        uint4* a = scr + (unit_on(G_PROBE + g * SLOT, (tid >> 5) & 1) + (j * 4 + (tid >> 6)) * 8);
        clr128((tid & 31) < 2, a + (tid & 31));
        if (settle((tid & 31) == 0, a)) __trap();
        uint32_t t;
        asm volatile("mov.u32 %0, %%clock;" : "=r"(t));
        sts32(sm + SM_RACE + ((tid >> 5) & 1) * 16 + (tid >> 6) * 4, t);
    }
    const int warp = __shfl_sync(0xffffffffu, tid >> 5, 0), lane = tid & 31;
    const int f0 = (g >> 1) * 576 + j * 64, fx = (g >> 1) * 576 + 448 + j * 16;
    const bool xg = j >= 4;

    if (warp == 8) {
        if (lane == 0) {
#pragma unroll
            for (int n = 0; n < 3; n++) mbar_init(bars + n * 8, 1);
            asm volatile("fence.mbarrier_init.release.cluster;" ::: "memory");
#pragma unroll
            for (int n = 0; n < 3; n++) {
                mbar_expect(bars + n * 8, cta < 108 ? 12288 : 0);
                if (cta < 108) tma3(sm + SM_W0 + n * 12288, &prm.m[M_WMOD], (cta % 36) * 16, n * 192, (cta / 36) * 2, bars + n * 8, pol);
            }
#pragma unroll
            for (int n = 3; n < 6 + NHARD; n++) if (n < CH_KV || n >= CH_KV + NFIRST) mbar_init(bars + n * 8, 1);
            asm volatile("fence.mbarrier_init.release.cluster;" ::: "memory");
        }
        __syncwarp();
        asm volatile("bar.arrive 5, 320;" ::: "memory");
        asm volatile("bar.sync 4, 96;" ::: "memory");
        if (lane == 0) {
#pragma unroll 1
            for (int n = 0; n < 3; n++) {
                mbar_expect(bars + (3 + n) * 8, 12288);
                mbar_wait(bars + (CH_KV + n / 2) * 8);
                tma3(sm + SM_W0 + (3 + n) * 12288, &prm.m[M_WQ], cta * 32, n * 192, 0, bars + (3 + n) * 8, pol);
            }
#pragma unroll 1
            for (int n = NFIRST; n < NHARD; n++) {
                mbar_expect(bars + (CH_KV + n) * 8, TILE_BYTES);
                mbar_wait(bars + (n - 1) * 8);
                tma3(sm + n * TILE_BYTES, &prm.m[M_K], 0, kv_row(n), 0, bars + (CH_KV + n) * 8, pol);
            }
        }
        __syncwarp();
        asm volatile("bar.sync 2, 64;" ::: "memory");
        if (sm & 1023) __trap();
        uint4 e = lds128(sm + SM_TAB + (6 + NHARD) * 16);
#pragma unroll 1
        for (int p = 6 + NHARD; p < NCHUNK; p++) {
            const uint4 nx = lds128(sm + SM_TAB + (p + 1) * 16);
            if (e.x & 0x80000u) {
                const uint32_t tb = bars + ((e.w >> ((lane & 3) * 8)) & 255) * 8;
#pragma unroll 1
                for (unsigned it = 0;; it++) {
                    uint32_t avg;
                    asm volatile("ld.volatile.shared.b32 %0, [%1];" : "=r"(avg) : "r"(sm + SM_ADJ) : "memory");
                    const bool far = avg >= (e.y >> 16);
                    if (__all_sync(0xffffffffu, mbar_test(tb) || ((lane & 3) == 3 && far))) break;
                    if (it > 16 * SPIN_LIMIT) __trap();
                }
                if (lane == 0) {
                    tma3(sm + (e.x & 0x7FFFF), &prm.m[(e.x >> 20) & 15], e.y & 0xFFFF, e.z & 0x3FFFF, 0, bars + (e.x >> 24) * 8, pol);
                }
            }
            e = nx;
        }
        return;
    }
    if (warp == 9) {
        if (lane < NMAPS)
            sts64(sm + SM_ORG + lane * 8,
                  lane <= M_V ? 0 : lane <= M_WQ ? cta * 32 : lane <= M_WD ? j * 64 : lane <= M_WU ? f0 : lane <= M_WDX ? 512 + j * 16 : fx,
                  (lane & 2) ? 0 : (lane & 1) ? g * 288 : g * 256);
        if (lane == 0) sts32(sm + SM_ADJ, 0);
        uint4 pe[4];
#pragma unroll
        for (int i = 0; i < 4; i++) pe[i] = __ldg(reinterpret_cast<const uint4*>(plan) + min(lane + 32 * i, NCHUNK - 1));
        if (lane == 0) {
#pragma unroll
            for (int n = 6 + NHARD; n < NBAR; n++) mbar_init(bars + n * 8, n >= REL && n < RELW ? 2 : 1);
            asm volatile("fence.mbarrier_init.release.cluster;" ::: "memory");
        }
        __syncwarp();
        asm volatile("bar.sync 4, 96;" ::: "memory");
#pragma unroll
        for (int i = 0; i < 4; i++) {
            if ((pe[i].y >> 16) == 0) {
                const uint32_t t = pe[i].y, h = t & 1;
                pe[i].x += xg ? (t - 2) * 6144 + (M_WGX << 20) : t < 2 ? h * 4096 + (M_WOX << 20) : 8192 + h * 4608 + (M_WDX << 20);
                pe[i].y = xg ? (t - 2 < 3 ? (t - 2) * 192 + (6144 << 16) : 0)
                             : t < 2 ? h * 128 + (4096 << 16) : t >= 4 ? h * 144 + (4608 << 16) : 0;
            }
            if (((pe[i].x >> 20) & 3) == 2 && (pe[i].x >> 24) >= CH_WO) pe[i].x += (g & 1) << 20;
            const int p = lane + 32 * i;
            if (p < NCHUNK) {
                const uint32_t org = sm + SM_ORG + ((pe[i].x >> 20) & 15) * 8;
                if (p >= 6 + NHARD) mbar_expect(bars + (pe[i].x >> 24) * 8, pe[i].y >> 16);
                sts128(sm + SM_TAB + p * 16, make_uint4(pe[i].x | ((pe[i].y >> 16) ? 0x80000u : 0u), lds32(org) | (pe[i].z << 16),
                                                        (((pe[i].x >> 20) & 15) <= M_V ? kv_row(pe[i].y & 0xFFFF) : lds32(org + 4) + (pe[i].y & 0xFFFF)) | (pe[i].z & 0xFFFC0000u), pe[i].w));
            }
        }
        asm volatile("bar.arrive 2, 64;" ::: "memory");
        __syncwarp();
        if (lane < NMAPS) asm volatile("prefetch.tensormap [%0];" ::"l"(&prm.m[lane]) : "memory");
        asm volatile("bar.sync 5, 320;" ::: "memory");
        unsigned* const cnt = reinterpret_cast<unsigned*>(scr + unit_on(G_CNT, near_side(sm)));
        unsigned* const cnt2 = reinterpret_cast<unsigned*>(reinterpret_cast<uintptr_t>(cnt) ^ 4096);
        if (lane == 0) {
            constexpr int NPACE = NCHUNK - 4;
            int n = 0;
            uint32_t kb = 0;
#pragma unroll 1
            for (unsigned it = 0; n < NPACE; it++) {
                while (n < NPACE && mbar_test(bars + (lds32(sm + SM_TAB + n * 16) >> 24) * 8)) n++;
                const uint32_t now = n == NPACE ? 2048 : n ? lds32(sm + SM_TAB + n * 16 - 8) >> 18 : 0;
                if (n == NPACE) pub32(atomicAdd(cnt2, now - kb) + now - kb == NCTA * 2048, cnt2, 0);
                else if (now != kb) asm volatile("red.relaxed.gpu.global.add.u32 [%0], %1;" ::"l"(cnt2), "r"(now - kb) : "memory");
                const uint32_t all = now == kb ? back32(true, cnt) : atomicAdd(cnt, now - kb);
                asm volatile("st.volatile.shared.b32 [%0], %1;" ::"r"(sm + SM_ADJ), "r"(all / NCTA) : "memory");
                pub32(all + now - kb == NCTA * 2048, cnt, 0);
                kb = now;
                if (it > SPIN_LIMIT) __trap();
            }
        }
        return;
    }
    if (warp >= 10) {
        asm volatile("bar.sync 9, 96;" ::: "memory");
        const int t = tid - 320;
        if (cta >= 36 && cta < 108) {
            constexpr int PER = (G_PART - G_STAT + 575) / 576 * 8;
            const int end = min(G_STAT + (cta - 35) * PER, G_PART);
#pragma unroll 4
            for (int i = G_STAT + (cta - 36) * PER + t; i < end; i += 64) clr128(true, scr + i);
        }
        const int part = unit_on(G_PART + cta * SLOT, near_side(sm));
#pragma unroll
        for (int i = 0; i < 256; i += 64) clr128(cta < 72, scr + (part + t + i));
        asm volatile("bar.sync 8, 64;" ::: "memory");
        asm volatile("fence.acq_rel.gpu;" ::: "memory");
        uint32_t* const mod = reinterpret_cast<uint32_t*>(scr + G_MOD);
        pub32(cta >= 36 && cta < 108, mod + (((cta / 72) * 2 + (warp & 1)) * 1152 + (cta % 36) * 32 + lane), lds32(sm + SM_MODW + t * 4));
        pub32(cta < 72 && t < 8, mod + (1152 * 4 + cta * 8 + t), part);
        return;
    }

    uint2 cw[3];
    uint32_t xw[9];
#pragma unroll
    for (int i = 0; i < 3; i++) cw[i] = cta < 108 ? __ldg(reinterpret_cast<const uint2*>(cvec) + min(tid + 256 * i, 575)) : make_uint2(0, 0);
#pragma unroll
    for (int i = 0; i < 9; i++) xw[i] = cta < 36 && warp >= 4 ? __ldg(reinterpret_cast<const uint32_t*>(x) + (warp & 3) * 288 + lane + 32 * i) : 0u;
    constexpr int QC = (G_STAT - G_Q) / 32;
    clr128(cta < 32 && tid < QC, scr + (G_Q + cta * QC + tid));
    const uint32_t cleared = settle(cta < 32 && tid < QC, scr + (G_Q + cta * QC + tid));
    const int mi = lane >> 3, r8 = lane & 7;
    const uint32_t bfrag = ((lane >> 2) & 3) * AV_PITCH + (lane & 3) * 4;
    uint32_t* const scr32 = reinterpret_cast<uint32_t*>(scr);
    uint2* const scr64 = reinterpret_cast<uint2*>(scr);
    const int pr = warp >> 1, hf = warp & 1;

#pragma unroll
    for (int i = 0; i < 3; i++) {
        const int p = min(tid + 256 * i, 575);
        const float a0 = bf_lo(cw[i].x), a1 = bf_hi(cw[i].x), a2 = bf_lo(cw[i].y), a3 = bf_hi(cw[i].y);
        sts64(sm + SM_AVA + (p / 144) * AV_PITCH + (p % 144) * 8, pack_bf(a0 * sigm(a0), a1 * sigm(a1)), pack_bf(a2 * sigm(a2), a3 * sigm(a3)));
    }
    if (cta < 36 && warp >= 4) {
        float mean_b, rden;
        ln_stats(xw, mean_b, rden);
        if (lane == 0) sts64(sm + SM_QS + (warp & 3) * 8, __float_as_uint(mean_b), __float_as_uint(rden));
#pragma unroll
        for (int i = 0; i < 9; i++) sts32(sm + SM_CB1 + (warp & 3) * 1152 + (lane + 32 * i) * 4, xw[i]);
    }
    asm volatile("bar.sync 5, 320;" ::: "memory");
    const int side = near_side(sm);
    auto vec576 = [&](int base) { return scr + (unit_on(base + ((g & 1) * 2 + (tid >= 144)) * SLOT, side) + tid - (tid >= 144) * 144); };
#pragma unroll 1
    for (int it = 0; it < 2; it++) {
        if (it == 1) {
            uint4 v[2];
            poll<2, 300>(v, vec576(G_H), 96, warp == 5 ? 0 : 2, [] {});
            put576(v, sm + SM_AVB, warp, tid);
            cbar();
        }
        if (cta < 108 || it == 1) {
            const int k = (mi >> 1) * 8 + r8;
            const uint32_t base = sm + SM_W0 + (it ? 36864 + k * 64 : (mi & 1) * 6144 + k * 32);
            const uint32_t ch = it ? (((mi & 1) * 2) ^ (r8 >> 1)) : (r8 >> 2);
            const uint32_t a0 = base + (ch << 4), a1 = base + ((ch ^ 1) << 4), kb = it ? 1024 : 512;
            const uint32_t bb = sm + (it ? SM_AVB : SM_AVA) + bfrag + warp * 32;
            float c0[4] = {0.f, 0.f, 0.f, 0.f}, c1[4] = {0.f, 0.f, 0.f, 0.f};
            uint32_t bq[5][2];
#pragma unroll
            for (int i = 0; i < 5; i++) { bq[i][0] = lds32(bb + i * 256); bq[i][1] = lds32(bb + i * 256 + 16); }
            if (warp >= 4) bq[4][0] = bq[4][1] = 0;
#pragma unroll
            for (int i = 0; i < 3; i++) mbar_wait(bars + (it * 3 + i) * 8);
#pragma unroll
            for (int i = 0; i < 5; i++) {
                const int ks = min(warp + 8 * i, 35);
                const int cq = ks / 12;
                const uint32_t off = cq * 12288 + (ks - cq * 12) * kb;
                uint32_t u[4], v[4];
                ldsm4t(u, a0 + off);
                ldsm4t(v, a1 + off);
                mma16816(c0, u, bq[i][0], bq[i][1]);
                mma16816(c1, v, bq[i][0], bq[i][1]);
            }
            if (cleared) __trap();
            const bool t1 = (lane & 2) != 0;
            sts128f(sm + SM_RED + warp * 512 + (t1 ? 256 : 0) + ((lane >> 2) * 2 + (lane & 1)) * 16,
                    t1 ? c1[0] : c0[0], t1 ? c1[1] : c0[1], t1 ? c1[2] : c0[2], t1 ? c1[3] : c0[3]);
            cbar();
            if (warp == 7) {
                const float4 r = sum8(sm + SM_RED + lane * 16, 512);
                if (it == 0 && cta < 36) {
                    const uint32_t xp = sm + SM_CB1 + (lane & 1) * 2304 + (cta * 16 + (lane >> 1)) * 2;
                    const float4 st = lds128f(sm + SM_QS + (lane & 1) * 16);
                    const float h0 = ln_mod(bf_lo(lds16(xp)), st.x, st.y, bfr(1.0f + bfr(r.z)), bfr(r.x));
                    const float h1 = ln_mod(bf_lo(lds16(xp + 1152)), st.z, st.w, bfr(1.0f + bfr(r.w)), bfr(r.y));
                    const uint32_t hv = enc(pack_bf(h0, h1));
#pragma unroll
                    for (int i = 0; i < 4; i++) pub32(true, scr32 + ((G_H + ((i >> 1) * 2 + cta / 18) * SLOT + (i & 1) * 256) * 4 + (cta % 18) * 32 + lane), hv);
                } else {
                    const uint32_t lo = enc(pack_bf(r.x, r.y)), hi = enc(pack_bf(r.z, r.w));
                    const int qd = unit_on(G_Q + (cta >> 4) * SLOT, side) * 4 + (cta & 15) * 64 + lane;
                    pub32(it, scr32 + qd, lo);
                    pub32(it, scr32 + qd + 32, hi);
                    pub32(it, scr32 + (qd ^ 1024), lo);
                    pub32(it, scr32 + (qd ^ 1024) + 32, hi);
                    if (it == 0) { sts32(sm + SM_MODW + lane * 4, lo); sts32(sm + SM_MODW + 128 + lane * 4, hi); }
                }
            }
        }
        if (tid == 192) mbar_arrive(bars + (RELW + it) * 8);
    }

    if (warp == 7) asm volatile("bar.arrive 9, 96;" ::: "memory");
    if (tid < 128) {
        uint4 v[1];
        poll<1, 40>(v, scr + (unit_on(G_Q + (g >> 1) * SLOT, side) + (g & 1) * 128 + tid), 0);
        put_piece(v[0], sm + SM_AVA + tid * 4);
    }
    cbar();
    uint32_t dst_part = 0;
    {
        auto fetch_mod = [&]() {
            if (warp < 5) {
                const int ob = min((warp < 4 ? j * 8 + warp * 2 : 64 + j * 2) + ((lane >> 1) & 1), 71);
#pragma unroll 1
                for (unsigned it = 0; !__all_sync(0xffffffffu, (dst_part = back32(true, scr32 + (G_UNIT * 4 + ob * 8))) != 0); it++)
                    if (it > SPIN_LIMIT) __trap();
                const int t = min(tid, 143);
                uint4 v[4];
                poll<4, 40>(v, scr + (G_MOD + 288 + t), 144);
#pragma unroll
                for (int i = 0; i < 4; i++) {
                    uint4 u = unzip(v[i]);
                    if (i >= 2) {
                        u.x = pack_bf(1.0f + bf_lo(u.x), 1.0f + bf_hi(u.x)); u.y = pack_bf(1.0f + bf_lo(u.y), 1.0f + bf_hi(u.y));
                        u.z = pack_bf(1.0f + bf_lo(u.z), 1.0f + bf_hi(u.z)); u.w = pack_bf(1.0f + bf_lo(u.w), 1.0f + bf_hi(u.w));
                    }
                    const uint32_t d = sm + (i >= 2 ? SM_CB1 : SM_SB) + (t + 144 * (i & 1)) * 4;
                    sts32(d, u.x); sts32(d + AV_PITCH, u.y); sts32(d + 2 * AV_PITCH, u.z); sts32(d + 3 * AV_PITCH, u.w);
                }
            } else if (warp == 7 && cta < 72) {
                sts16(sm + SM_XR + (lane & 7) * 8 + (lane >> 3) * 2,
                      reinterpret_cast<const unsigned short*>(x)[(lane >> 3) * D_MODEL + cta * 8 + (lane & 7)]);
                uint4 v[2];
                poll<2, 40>(v, scr + (G_MOD + cta * 4 + ((lane & 7) >> 1)), 864);
                sts128(sm + SM_QS + (lane & 7) * 16, make_uint4(~((lane & 1) ? v[0].z : v[0].x), ~((lane & 1) ? v[0].w : v[0].y),
                                                                ~((lane & 1) ? v[1].z : v[1].x), ~((lane & 1) ? v[1].w : v[1].y)));
            }
        };
        const uint32_t koff = (hf * 32 + (mi & 1) * 8 + r8) * 128;
        uint32_t sw[4];
#pragma unroll
        for (int c = 0; c < 4; c++) sw[c] = koff + (((2 * c + (mi >> 1)) ^ r8) << 4);
#pragma unroll 1
        for (int i = pr; i < TILES; i += 4) {
            uint32_t qf[8][2];
#pragma unroll
            for (int ks = 0; ks < 8; ks++) {
                const uint32_t a = sm + SM_AVA + (i >> 3) * AV_PITCH + ((lane >> 2) & 1) * 256 + ks * 32 + (lane & 3) * 4;
                qf[ks][0] = lds32(a); qf[ks][1] = lds32(a + 16);
            }
            mbar_wait(bars + (CH_KV + i) * 8);
            const uint32_t tb = sm + (i % NSLOT) * TILE_BYTES;
            float c[4][4];
#pragma unroll
            for (int u = 0; u < 4; u++) { c[u][0] = c[u][1] = c[u][2] = c[u][3] = 0.f; }
#pragma unroll
            for (int ks = 0; ks < 4; ks++) {
#pragma unroll
                for (int u = 0; u < 4; u++) {
                    uint32_t a[4];
                    ldsm4(a, tb + (u >> 1) * 8192 + (u & 1) * 2048 + sw[ks]);
                    mma16816(c[u], a, qf[(u >> 1) * 4 + ks][0], qf[(u >> 1) * 4 + ks][1]);
                }
            }
            __syncwarp();
            if (lane == 0) mbar_arrive(bars + (REL + i) * 8);
            const bool t1 = (lane & 2) != 0, hi = (lane & 1) != 0;
            const float p0 = t1 ? (hi ? c[1][2] + c[3][2] : c[1][0] + c[3][0]) : (hi ? c[0][2] + c[2][2] : c[0][0] + c[2][0]);
            const float p1 = t1 ? (hi ? c[1][3] + c[3][3] : c[1][1] + c[3][1]) : (hi ? c[0][3] + c[2][3] : c[0][1] + c[2][1]);
            const uint32_t w = pack_bf(bfr(p0) * 0.08838834764831845f, bfr(p1) * 0.08838834764831845f);
            const uint32_t a = sm + SM_SC + (i * 64 + hf * 32 + (lane & 3) * 8 + (lane >> 2)) * 2;
            sts16(a, w & 0xFFFFu);
            sts16(a + 4096, w >> 16);
            if ((i >> 2) == 4 + cta % 3) fetch_mod();
        }
    }
    cbar();

    {
        const uint32_t a = sm + SM_SC + tid * 32;
        const uint4 u0 = lds128(a), u1 = lds128(a + 16);
        const uint32_t w[8] = {u0.x, u0.y, u0.z, u0.w, u1.x, u1.y, u1.z, u1.w};
        float e[16], m = -INFINITY;
#pragma unroll
        for (int i = 0; i < 8; i++) { e[2 * i] = bf_lo(w[i]); e[2 * i + 1] = bf_hi(w[i]); m = fmaxf(m, fmaxf(e[2 * i], e[2 * i + 1])); }
#pragma unroll
        for (int o = 16; o; o >>= 1) m = fmaxf(m, __shfl_xor_sync(0xffffffffu, m, o));
        float l = 0.f;
#pragma unroll
        for (int i = 0; i < 16; i++) { e[i] = ex2((e[i] - m) * LOG2E); l += e[i]; }
#pragma unroll
        for (int o = 16; o; o >>= 1) l += __shfl_xor_sync(0xffffffffu, l, o);
        if (lane == 0) sts64(sm + SM_RED + warp * 8, encf(m), encf(l));
        cbar();
        if (warp == 0) {
            pub32(true, scr32 + ((G_STAT + (cta >> 5) * SLOT + (lane >> 4) * 256 + (cta & 31) * 8) * 4 + (lane & 15)), lds32(sm + SM_RED + (lane & 15) * 4));
            uint4 v[1];
            poll<1, 40>(v, scr + (unit_on(G_STAT + (g >> 2) * SLOT, side) + ((g & 3) * 8 + (lane >> 2)) * 8 + (lane & 3)), 0);
            const float ma = decf(v[0].x), mb = decf(v[0].z);
            float ga = ma, gb = mb;
#pragma unroll
            for (int o = 4; o < 32; o <<= 1) { ga = fmaxf(ga, __shfl_xor_sync(0xffffffffu, ga, o)); gb = fmaxf(gb, __shfl_xor_sync(0xffffffffu, gb, o)); }
            float la = decf(v[0].y) * ex2((ma - ga) * LOG2E), lb = decf(v[0].w) * ex2((mb - gb) * LOG2E);
#pragma unroll
            for (int o = 4; o < 32; o <<= 1) { la += __shfl_xor_sync(0xffffffffu, la, o); lb += __shfl_xor_sync(0xffffffffu, lb, o); }
            sts128f(sm + SM_RED + 64 + (lane & 3) * 16, ga, rcp(la), gb, rcp(lb));
        }
        cbar();
        const float f = ex2((m - ldsf(sm + SM_RED + 64 + warp * 8)) * LOG2E) * ldsf(sm + SM_RED + 68 + warp * 8);
        uint4 o0, o1;
        o0.x = pack_bf(e[0] * f, e[1] * f); o0.y = pack_bf(e[2] * f, e[3] * f); o0.z = pack_bf(e[4] * f, e[5] * f); o0.w = pack_bf(e[6] * f, e[7] * f);
        o1.x = pack_bf(e[8] * f, e[9] * f); o1.y = pack_bf(e[10] * f, e[11] * f); o1.z = pack_bf(e[12] * f, e[13] * f); o1.w = pack_bf(e[14] * f, e[15] * f);
        sts128(a, o0); sts128(a + 16, o1);
        cbar();
    }

    const int my_part = unit_on(G_PART + cta * SLOT, side);
    uint32_t wa[2][18][4];
    const bool pw = warp < 4 || (warp == 4 && j < 4);
    const uint32_t astep = warp < 4 ? 2048 : 512;
    const uint32_t aoff = warp < 4 ? ((mi >> 1) * 8 + r8) * 128 + (((warp * 2 + (mi & 1)) ^ r8) << 4)
                                   : ((mi >> 1) * 8 + r8) * 32 + (((mi & 1) ^ (r8 >> 2)) << 4);
    const uint32_t abase[2] = {sm + (warp < 4 ? SM_WO : SM_X) + aoff, sm + (warp < 4 ? SM_WD : SM_X + 8192) + aoff};
    int nl = 0;
    auto proj_bar = [&](int rd) {
        const int c = min(lane, 3 + 2 * rd);
        return bars + (warp < 4 ? (rd ? CH_WD : CH_WO) + c : CH_X + 4 * rd + c / (2 + rd)) * 8;
    };
    auto proj_more = [&](int rd, bool t) {
        const int nr = min(__ffs(~__ballot_sync(0xffffffffu, t) | 0x100) - 1, 4 + 2 * rd);
        if (nr > nl) {
#pragma unroll
            for (int c = 0; c < 4 + 2 * rd; c++) {
                if (c >= nl && c < nr) {
#pragma unroll
                    for (int u = c * (4 - rd); u < (c + 1) * (4 - rd); u++) ldsm4t(wa[rd][u], abase[rd] + u * astep);
                }
            }
            nl = nr;
        }
    };
    {
        float o[4][4];
#pragma unroll
        for (int u = 0; u < 4; u++) { o[u][0] = o[u][1] = o[u][2] = o[u][3] = 0.f; }
        const uint32_t voff = hf * 8192 + ((mi >> 1) * 8 + r8) * 128;
        uint32_t sw[4];
#pragma unroll
        for (int u = 0; u < 4; u++) sw[u] = voff + (((2 * u + (mi & 1)) ^ r8) << 4);
        const uint32_t pb = sm + SM_SC + ((lane >> 2) & 1) * 4096 + (lane & 3) * 4 - TILES * 128;
        auto v_tile = [&](int i) {
            uint32_t pf[4][2];
#pragma unroll
            for (int kk = 0; kk < 4; kk++) { pf[kk][0] = lds32(pb + i * 128 + kk * 32); pf[kk][1] = lds32(pb + i * 128 + kk * 32 + 16); }
            const uint32_t tb = sm + (i % NSLOT) * TILE_BYTES;
            mbar_wait(bars + (CH_KV + i) * 8);
#pragma unroll
            for (int kk = 0; kk < 4; kk++) {
#pragma unroll
                for (int u = 0; u < 4; u++) {
                    uint32_t a[4];
                    ldsm4t(a, tb + kk * 2048 + sw[u]);
                    mma16816(o[u], a, pf[kk][0], pf[kk][1]);
                }
            }
            __syncwarp();
            if (lane == 0) mbar_arrive(bars + (REL + i) * 8);
        };
#pragma unroll 1
        for (int t = 0; t <= 8; t++) {
            const int gb = t == 8 ? 3 : (t & 1) ? (t - 3) >> 1 : -1;
            bool todo = t < 8;
            uint4 v[2];
            const int osrc = t == 8 ? unit_on(G_O3 + (g * 2 + ((lane >> 1) & 1)) * SLOT, side) + (lane & 1) * 128
                                    : G_OPART + (gb * NCTA + g * 8 + (lane & 3) * 2) * 64;
            poll<2, 0>(v, scr + (osrc + (tid >> 2)), 64, gb < 0 ? 3 : 0, [&] {
                if (todo) {
                    v_tile(TILES + pr + 4 * t);
                    if (t & 1) {
                        const int u = lane & 3;
                        const uint32_t red = sm + ((t & 2) ? SM_RED : SM_AVB);
                        const uint32_t a = red + pr * 1024 + (hf * 64 + u * 16 + (lane >> 2)) * 4;
                        float w[4];
#pragma unroll
                        for (int q = 0; q < 4; q++) w[q] = u == 0 ? o[0][q] : u == 1 ? o[1][q] : u == 2 ? o[2][q] : o[3][q];
                        stsf(a, w[0]); stsf(a + 512, w[1]); stsf(a + 32, w[2]); stsf(a + 512 + 32, w[3]);
#pragma unroll
                        for (int q = 0; q < 4; q++) { o[q][0] = o[q][1] = o[q][2] = o[q][3] = 0.f; }
                        cbar();
                        const uint32_t r = red + tid * 4;
                        const uint32_t ov = encf((ldsf(r) + ldsf(r + 1024)) + (ldsf(r + 2048) + ldsf(r + 3072)));
                        const int od = t == 7 ? unit_on(G_O3 + (cta >> 2) * SLOT, side) + (cta & 3) * 64 : G_OPART + ((t >> 1) * NCTA + cta) * 64;
                        pub32(true, scr32 + (od * 4 + tid), ov);
                        pub32(t == 7, scr32 + ((od ^ 256) * 4 + tid), ov);
                    }
                } else if (warp < 5 && nl < 4) proj_more(0, mbar_test(proj_bar(0)));
                todo = false;
            });
            if (gb >= 0) {
                const bool od = lane & 1;
                const float s0 = decf(v[0].x) + decf(v[1].x), s1 = decf(v[0].y) + decf(v[1].y);
                const float s2 = decf(v[0].z) + decf(v[1].z), s3 = decf(v[0].w) + decf(v[1].w);
                float a0 = (od ? s2 : s0) + __shfl_xor_sync(0xffffffffu, od ? s0 : s2, 1);
                float a1 = (od ? s3 : s1) + __shfl_xor_sync(0xffffffffu, od ? s1 : s3, 1);
                a0 += __shfl_xor_sync(0xffffffffu, a0, 2);
                a1 += __shfl_xor_sync(0xffffffffu, a1, 2);
                sts32(sm + SM_AVA + gb * AV_PITCH + (tid >> 2) * 8 + (lane & 1) * 4, pack_bf(a0, a1));
            }
        }
    }

    auto project = [&](int rd) {
        uint2* dst = scr64 + ((dst_part + rd * 128 + g * 8) * 2 + (lane >> 2) * 2 + (lane & 1));
        asm volatile("" : "+l"(dst));
        uint32_t b4[9][4];
#pragma unroll
        for (int u = 0; u < 8 + rd; u++) ldsm4(b4[u], sm + SM_AVA + (r8 & 3) * AV_PITCH + mi * 16 + u * 64);
        float c[4][4];
#pragma unroll
        for (int u = 0; u < 4; u++) { c[u][0] = c[u][1] = c[u][2] = c[u][3] = 0.f; }
        if (__builtin_expect(nl < 3 + 2 * rd, 0)) {
#pragma unroll 1
            for (unsigned it = 0; nl < 3 + 2 * rd; it++) {
                proj_more(rd, mbar_test(proj_bar(rd)));
                if (it > 16 * SPIN_LIMIT) __trap();
            }
        }
#pragma unroll
        for (int u = 0; u < 12 + 3 * rd; u++) mma16816(c[u & 3], wa[rd][u], b4[u >> 1][(u & 1) * 2], b4[u >> 1][(u & 1) * 2 + 1]);
        if (nl < 4 + 2 * rd) {
            mbar_wait(bars + (warp < 4 ? (rd ? CH_WD + 5 : CH_WO + 3) : CH_X + 4 * rd + 1) * 8);
#pragma unroll
            for (int u = 12 + 3 * rd; u < 16 + 2 * rd; u++) ldsm4t(wa[rd][u], abase[rd] + u * astep);
        }
#pragma unroll
        for (int u = 12 + 3 * rd; u < 16 + 2 * rd; u++) mma16816(c[u & 3], wa[rd][u], b4[u >> 1][(u & 1) * 2], b4[u >> 1][(u & 1) * 2 + 1]);
        const bool hi = (lane & 2) != 0;
        pub64(pw, dst,
              encf(hi ? (c[2][2] + c[3][2]) + (c[0][2] + c[1][2]) : (c[2][0] + c[3][0]) + (c[0][0] + c[1][0])),
              encf(hi ? (c[2][3] + c[3][3]) + (c[0][3] + c[1][3]) : (c[2][1] + c[3][1]) + (c[0][1] + c[1][1])));
    };
    auto reduce = [&](int rd) {
        const uint32_t g01 = lds32(sm + SM_QS + (lane & 7) * 16 + rd * 8), g23 = lds32(sm + SM_QS + (lane & 7) * 16 + rd * 8 + 4);
        const uint32_t r01 = lds32(sm + SM_XR + (lane & 7) * 8), r23 = lds32(sm + SM_XR + 4 + (lane & 7) * 8);
        void* dst = rd ? (void*)(out + ((lane >> 3) * D_MODEL + cta * 8 + (lane & 7)))
                       : (void*)(scr64 + ((G_X1 + ((lane >> 4) * 2 + cta / 36) * SLOT + ((lane >> 3) & 1) * 256) * 2 + (cta % 36) * 8 + (lane & 7)));
        asm volatile("" : "+l"(dst));
        uint4 w[4];
        poll<4, 0>(w, scr + (my_part + rd * 128 + lane), 32);
        float t[4] = {(decf(w[0].x) + decf(w[1].x)) + (decf(w[2].x) + decf(w[3].x)), (decf(w[0].y) + decf(w[1].y)) + (decf(w[2].y) + decf(w[3].y)),
                      (decf(w[0].z) + decf(w[1].z)) + (decf(w[2].z) + decf(w[3].z)), (decf(w[0].w) + decf(w[1].w)) + (decf(w[2].w) + decf(w[3].w))};
#pragma unroll
        for (int q = 0; q < 4; q++) t[q] += __shfl_xor_sync(0xffffffffu, t[q], 8);
#pragma unroll
        for (int q = 0; q < 4; q++) t[q] += __shfl_xor_sync(0xffffffffu, t[q], 16);
        const uint32_t x01 = add2(r01, mul2(g01, pack_bf(t[0], t[1]))), x23 = add2(r23, mul2(g23, pack_bf(t[2], t[3])));
        if (rd == 1) {
            const uint32_t ov = (lane & 16) ? x23 : x01;
            st16(true, dst, (lane & 8) ? ov >> 16 : ov);
        } else {
            pub64(true, dst, enc(x01), enc(x23));
            sts64(sm + SM_XR + (lane & 7) * 8, x01, x23);
        }
    };
    arrive_if<6>(warp >= 5);
    if (__builtin_expect(warp < 5, 1)) {
        await<6>();
        project(0);
    } else if (warp == 7 && cta < 72) {
        reduce(0);
    }
    {
        uint32_t wg[5][5][4];
        const bool four = warp >= 4;
        uint32_t gbar;
        {
            const int ks = min(warp + 8 * (lane >> 1), 35);
            gbar = bars + ((xg && (lane & 1)) ? CH_X + 2 + ks / 12 : CH_GU + ks / 3) * 8;
        }
        const int nw = four ? 4 : 5;
        auto gu_load = [&](int i) {
            const int k = (warp + 8 * i) * 16 + (mi >> 1) * 8 + r8;
#pragma unroll
            for (int u = 0; u < 4; u++) ldsm4t(wg[i][u], sm + SM_WG + k * 128 + (((2 * u + (mi & 1)) ^ r8) << 4));
            if (xg) ldsm4t(wg[i][4], sm + SM_X + k * 32 + (((mi & 1) ^ (r8 >> 2)) << 4));
        };
        auto gu_more = [&](bool t) {
            const int nr = min((__ffs(~__ballot_sync(0xffffffffu, t) | 0x400) - 1) >> 1, nw);
            if (nr > nl) {
#pragma unroll
                for (int i = 0; i < 5; i++) if (i >= nl && i < nr) gu_load(i);
                nl = nr;
            }
        };
        nl = 0;
        {
            uint4 v[2];
            poll_test<2>(v, vec576(G_X1), 96, warp == 5 ? 0 : 2, gbar, gu_more);
            put576(v, sm + SM_AVB, warp, tid);
        }
        cbar();
        uint32_t bq[5][2];
        {
            const uint32_t fo = bfrag + warp * 32;
#pragma unroll
            for (int i = 0; i < 5; i++) { bq[i][0] = lds32(sm + SM_AVB + fo + i * 256); bq[i][1] = lds32(sm + SM_AVB + fo + i * 256 + 16); }
            const uint32_t piv2 = lane < 16 ? 0u : __byte_perm(lds32(sm + SM_AVB + ((lane >> 2) & 3) * AV_PITCH), 0, 0x1010);
            float m0[4] = {0.f, 0.f, 0.f, 0.f}, m1[4] = {0.f, 0.f, 0.f, 0.f};
#pragma unroll
            for (int i = 0; i < 5; i++) {
                uint32_t d[4] = {sub2(bq[i][0], piv2), 0x3F803F80u, sub2(bq[i][1], piv2), 0x3F803F80u};
                if (i == 4 && four) d[0] = d[2] = 0;
                mma16816((i & 1) ? m1 : m0, d, d[0], d[2]);
            }
            sts64_if((lane & 3) == (lane >> 3), sm + SM_RED + (lane >> 2) * 80 + warp * 8,
                     (lane & 4) ? m0[3] + m1[3] : m0[2] + m1[2], (lane & 4) ? m0[1] + m1[1] : m0[0] + m1[0]);
            cbar();
            const uint32_t ra = sm + SM_RED + (lane >> 2) * 80;
            const float4 p0 = lds128f(ra), p1 = lds128f(ra + 16), p2 = lds128f(ra + 32), p3 = lds128f(ra + 48);
            const float sd = (((p0.x + p0.z) + (p1.x + p1.z)) + ((p2.x + p2.z) + (p3.x + p3.z))) * (1.0f / D_MODEL);
            const float sq = ((p0.y + p0.w) + (p1.y + p1.w)) + ((p2.y + p2.w) + (p3.y + p3.w));
            float mean = bf_hi(piv2) + sd, var = fmaf(sq, 1.0f / D_MODEL, -sd * sd);
            const float mean_o = __shfl_xor_sync(0xffffffffu, mean, 16), var_o = __shfl_xor_sync(0xffffffffu, var, 16);
            uint32_t c1[5][2], sb[5][2];
#pragma unroll
            for (int i = 0; i < 5; i++) {
                c1[i][0] = lds32(sm + SM_CB1 + fo + i * 256); c1[i][1] = lds32(sm + SM_CB1 + fo + i * 256 + 16);
                sb[i][0] = lds32(sm + SM_SB + fo + i * 256); sb[i][1] = lds32(sm + SM_SB + fo + i * 256 + 16);
            }
            const float mean_r = lane < 16 ? mean : mean_o, var_r = lane < 16 ? var : var_o;
            if ((mean_r * mean_r > 16.0f * var_r) == (lane < 16)) { mean = mean_o; var = var_o; }
            const float mean_b = bfr(mean), rden = ln_rden(var);
            const uint32_t mean2 = __byte_perm(__float_as_uint(mean_b), 0, 0x3232);
#pragma unroll
            for (int i = 0; i < 5; i++) {
                bq[i][0] = ln_mod2(bq[i][0], mean2, rden, c1[i][0], sb[i][0]);
                bq[i][1] = ln_mod2(bq[i][1], mean2, rden, c1[i][1], sb[i][1]);
            }
        }
        {
            float c[5][4];
#pragma unroll
            for (int u = 0; u < 5; u++) { c[u][0] = c[u][1] = c[u][2] = c[u][3] = 0.f; }
            if (__builtin_expect(nl < 3, 0)) {
#pragma unroll 1
                for (unsigned it = 0; nl < 3; it++) {
                    gu_more(mbar_test(gbar));
                    if (it > 16 * SPIN_LIMIT) __trap();
                }
            }
#pragma unroll
            for (int i = 0; i < 5; i++) {
                if (i < 4 || !four) {
                    if (i >= 3 && nl <= i) {
#pragma unroll 1
                        for (unsigned it = 0; ((__ballot_sync(0xffffffffu, mbar_test(gbar)) >> (2 * i)) & 3) != 3; it++)
                            if (it > 16 * SPIN_LIMIT) __trap();
                        gu_load(i);
                    }
#pragma unroll
                    for (int u = 0; u < 4; u++) mma16816(c[u], wg[i][u], bq[i][0], bq[i][1]);
                    if (xg) mma16816(c[4], wg[i][4], bq[i][0], bq[i][1]);
                }
            }
            const bool t1 = (lane & 2) != 0;
            const uint32_t rb = sm + SM_GRED + warp * 1280 + ((lane >> 2) * 2 + (lane & 1)) * 16;
#pragma unroll
            for (int u = 0; u < 4; u += 2)
                sts128f(rb + (t1 ? 256 : 0) + u * 256, t1 ? c[u + 1][0] : c[u][0], t1 ? c[u + 1][1] : c[u][1], t1 ? c[u + 1][2] : c[u][2], t1 ? c[u + 1][3] : c[u][3]);
            sts128f(rb + 1024, c[4][0], c[4][1], c[4][2], c[4][3]);
            arrive_if<7>(warp < 5);
        }
        if (__builtin_expect(warp >= 5, 1)) {
            const int t = tid - 160;
            const int col = t < 64 ? f0 + (t >> 4) * 16 : fx;
            uint32_t* ad0 = scr32 + (unit_on(G_ACT + ((g & 1) * 9 + (col >> 9)) * SLOT, side) * 4 + (col & 511) * 2 + (t & 15));
            uint32_t* ad1 = reinterpret_cast<uint32_t*>(reinterpret_cast<uintptr_t>(ad0) ^ 4096);
            asm volatile("" : "+l"(ad0), "+l"(ad1));
            await<7>();
            float4 r = sum8(sm + SM_GRED + min(t, 79) * 16, 1280);
            if ((g & 1) == 0) { r.x = gelu(bfr(r.x)); r.y = gelu(bfr(r.y)); r.z = gelu(bfr(r.z)); r.w = gelu(bfr(r.w)); }
            const uint32_t lo = enc(pack_bf(r.x, r.y)), hi = enc(pack_bf(r.z, r.w));
            pub32(t < (xg ? 80 : 64), ad0, lo);
            pub32(t < (xg ? 80 : 64), ad0 + 16, hi);
            pub32(t < (xg ? 80 : 64), ad1, lo);
            pub32(t < (xg ? 80 : 64), ad1 + 16, hi);
            static_assert(G_UNIT + 144 - G_H <= NCTA * 32, "clear split");
            clr128(t < 32 && G_H + cta * 32 + t < G_UNIT + 144, scr + (G_H + cta * 32 + t));
            if (warp == 7 && cta < 72) reduce(1);
        } else {
            nl = 0;
            uint4 v[2];
            const int t = min(tid, 143);
            const int pc = g * 144 + t;
            const int a0 = unit_on(G_ACT + (pc >> 8) * SLOT, side), a1 = unit_on(G_ACT + (9 + (pc >> 8)) * SLOT, side);
            poll_test<2>(v, scr + (a0 + (pc & 255)), a1 - a0, 0, proj_bar(1), [&](bool ok) { proj_more(1, ok); });
            put_piece(make_uint4(~mul2(~v[0].x, ~v[1].x), ~mul2(~v[0].y, ~v[1].y), ~mul2(~v[0].z, ~v[1].z), ~mul2(~v[0].w, ~v[1].w)),
                      sm + SM_AVA + t * 4);
            asm volatile("bar.sync 3, 160;" ::: "memory");
            project(1);
        }
    }
}

typedef CUresult (*EncodeFn)(CUtensorMap*, CUtensorMapDataType, cuuint32_t, void*, const cuuint64_t*, const cuuint64_t*,
                             const cuuint32_t*, const cuuint32_t*, CUtensorMapInterleave, CUtensorMapSwizzle,
                             CUtensorMapL2promotion, CUtensorMapFloatOOBfill);

void make3d(EncodeFn fn, CUtensorMap* m, const void* p, uint64_t d0, uint64_t d1, uint64_t d2, uint64_t s1, uint64_t s2,
            uint32_t b0, uint32_t b1, uint32_t b2, CUtensorMapSwizzle sw, CUtensorMapL2promotion promo) {
    cuuint64_t gd[3] = {d0, d1, d2};
    cuuint64_t gs[2] = {s1, s2};
    cuuint32_t bx[3] = {b0, b1, b2};
    cuuint32_t es[3] = {1, 1, 1};
    fn(m, CU_TENSOR_MAP_DATA_TYPE_BFLOAT16, 3, const_cast<void*>(p), gd, gs, bx, es, CU_TENSOR_MAP_INTERLEAVE_NONE, sw, promo,
       CU_TENSOR_MAP_FLOAT_OOB_FILL_NONE);
}

}

extern "C" void kernel_launch(void* const* d_in, const int* in_sizes, int n_in, void* d_out, int out_size) {
    (void)in_sizes; (void)n_in; (void)out_size;
    EncodeFn fn = nullptr;
    cudaDriverEntryPointQueryResult qr;
    cudaGetDriverEntryPoint("cuTensorMapEncodeTiled", (void**)&fn, cudaEnableDefault, &qr);
    cudaFuncSetAttribute(fused_block_kernel, cudaFuncAttributeMaxDynamicSharedMemorySize, SM_TOTAL);
    Params prm;
    const CUtensorMapL2promotion P128 = CU_TENSOR_MAP_L2_PROMOTION_L2_128B, P256 = CU_TENSOR_MAP_L2_PROMOTION_L2_256B;
    make3d(fn, &prm.m[M_K], d_in[1], 64, (uint64_t)NB * 16 * SK, 2, 256, 128, 64, 64, 2, CU_TENSOR_MAP_SWIZZLE_128B, P256);
    make3d(fn, &prm.m[M_V], d_in[2], 64, (uint64_t)NB * 16 * SK, 2, 256, 128, 64, 64, 2, CU_TENSOR_MAP_SWIZZLE_128B, P256);
    make3d(fn, &prm.m[M_WMOD], d_in[10], D_MODEL, D_MODEL, 6, 6 * D_MODEL * 2, D_MODEL * 2, 16, 192, 2, CU_TENSOR_MAP_SWIZZLE_32B, P128);
    make3d(fn, &prm.m[M_WQ], d_in[3], 4096, D_MODEL, 1, 8192, 8192 * D_MODEL, 32, 192, 1, CU_TENSOR_MAP_SWIZZLE_64B, P128);
    for (int x = 0; x < 2; x++) {
        const CUtensorMapSwizzle sp = x ? CU_TENSOR_MAP_SWIZZLE_32B : CU_TENSOR_MAP_SWIZZLE_128B;
        make3d(fn, &prm.m[M_WO + 4 * x], d_in[4], D_MODEL, 4096, 1, D_MODEL * 2, D_MODEL * 2 * 4096, x ? 16 : 64, x ? 128 : 64, 1, sp, P128);
        make3d(fn, &prm.m[M_WD + 4 * x], d_in[8], D_MODEL, FF, 1, D_MODEL * 2, D_MODEL * 2 * FF, x ? 16 : 64, x ? 144 : 48, 1, sp, P128);
        make3d(fn, &prm.m[M_WG + 4 * x], d_in[6], FF, D_MODEL, 1, FF * 2, FF * 2 * D_MODEL, x ? 16 : 64, x ? 192 : 48, 1, sp, P128);
        make3d(fn, &prm.m[M_WU + 4 * x], d_in[7], FF, D_MODEL, 1, FF * 2, FF * 2 * D_MODEL, x ? 16 : 64, x ? 192 : 48, 1, sp, P128);
    }
    void* scr = nullptr;
    void* plan = nullptr;
    cudaGetSymbolAddress(&scr, g_scr);
    cudaGetSymbolAddress(&plan, g_plan);
    scr = (void*)(((uintptr_t)scr + (2 << 20) - 1) & ~(uintptr_t)((2 << 20) - 1));
    cudaLaunchConfig_t cfg = {};
    cfg.gridDim = dim3(NCTA); cfg.blockDim = dim3(NTHREADS); cfg.dynamicSmemBytes = SM_TOTAL; cfg.stream = cudaStreamPerThread;
    cudaLaunchAttribute at[1];
    at[0].id = cudaLaunchAttributeCooperative; at[0].val.cooperative = 1;
    cfg.attrs = at; cfg.numAttrs = 1;
    cudaLaunchKernelEx(&cfg, fused_block_kernel, (const __nv_bfloat16*)d_in[0], (const __nv_bfloat16*)d_in[9],
                       (__nv_bfloat16*)d_out, (uint4*)scr, (const void*)plan, prm);
}
```
